```python
import torch

def _softmax(x, axis=-1):
    return torch.softmax(x, dim=axis)
def _gelu(x):
    return torch.nn.functional.gelu(x, approximate="tanh")
def _silu(x):
    return torch.nn.functional.silu(x)
def _sigmoid(x):
    return torch.sigmoid(x)
def _layernorm(x, axis=-1, eps=1e-5):
    m = x.mean(dim=axis, keepdim=True)
    v = x.var(dim=axis, keepdim=True, unbiased=False)
    return (x - m) / torch.sqrt(v + eps)
def _scatter_add(tgt, idx, src, axis=0):
    return tgt.clone().index_add_(axis, idx, src)
def _segment_sum(src, seg, n):
    out = torch.zeros((n,) + src.shape[1:], dtype=src.dtype)
    return out.index_add_(0, seg, src)
def _pad(x, pw):
    flat = tuple(v for pair in reversed(pw) for v in pair)
    return torch.nn.functional.pad(x, flat)

kernel_name = 'parallel_sum__compressed_kv_cla__glu_gated_glu__decode'

def setup_inputs():

    _w = (lambda a: (lambda t: t.to(torch.bfloat16) if t.is_floating_point() else t)(torch.as_tensor(a)))
    def _A_setup():
        B, H, Sq, Sk, D, M = 2, 32, 1, 4096, 128, 512
        Dc = 4 * D
        return {
            "x": _w((lambda *s: torch.randn(*s, dtype=torch.bfloat16) * 0.05)(B, Sq, M)),
            "c_kv": _w((lambda *s: torch.randn(*s, dtype=torch.bfloat16) * 1.6)(B, Sk, Dc)),
            "w_q": _w((lambda *s: torch.randn(*s, dtype=torch.bfloat16) * 1.6)(M, H, D) * (M ** -0.5)),
            "w_uk": _w((lambda *s: torch.randn(*s, dtype=torch.bfloat16) * 1.6)(Dc, H, D) * (Dc ** -0.5)),
            "w_uv": _w((lambda *s: torch.randn(*s, dtype=torch.bfloat16) * 1.6)(Dc, H, D) * (Dc ** -0.5)),
            "w_o": _w((lambda *s: torch.randn(*s, dtype=torch.bfloat16) * 1.6)(H, D, M) * ((H * D) ** -0.5)),
        }
    _A_in = _A_setup()

    def _B_setup():
        B, S, D, F = 2, 1, 512, 1376
        return {
            "x": _w((lambda *s: torch.randn(*s, dtype=torch.bfloat16) * 0.05)(B, S, D)),
            "w_gate": _w((lambda *s: torch.randn(*s, dtype=torch.bfloat16) * 0.1)(D, F)),
            "w_up": _w((lambda *s: torch.randn(*s, dtype=torch.bfloat16) * 0.05)(D, F)),
            "w_down": _w((lambda *s: torch.randn(*s, dtype=torch.bfloat16) * 0.05)(F, D)),
        }
    _B_in = _B_setup()

    return {
        "A_x": _A_in["x"],
        "A_c_kv": _A_in["c_kv"],
        "A_w_q": _A_in["w_q"],
        "A_w_uk": _A_in["w_uk"],
        "A_w_uv": _A_in["w_uv"],
        "A_w_o": _A_in["w_o"],
        "B_x": _B_in["x"],
        "B_w_gate": _B_in["w_gate"],
        "B_w_up": _B_in["w_up"],
        "B_w_down": _B_in["w_down"],
    }

def reference(A_x, A_c_kv, A_w_q, A_w_uk, A_w_uv, A_w_o, B_x, B_w_gate, B_w_up, B_w_down):
    def _A_ref(x, c_kv, w_q, w_uk, w_uv, w_o):
        B, Sq, M = x.shape[0], x.shape[1], x.shape[2]
        Sk = c_kv.shape[1]
        H, D = w_q.shape[1], w_q.shape[2]
        q = torch.einsum("bqm,mhd->bhqd", x, w_q)
        k = torch.einsum("bkc,chd->bhkd", c_kv, w_uk)
        v = torch.einsum("bkc,chd->bhkd", c_kv, w_uv)
        scores = torch.einsum("bhqd,bhkd->bhqk", q, k) * (D ** -0.5)
        off = Sk - Sq
        qi = torch.arange(Sq)[:, None]
        kj = torch.arange(Sk)[None, :]
        cmask = kj <= (qi + off)
        scores = torch.where(cmask[None, None], scores, -1e9)
        p = _softmax(scores, axis=-1)
        ctx = torch.einsum("bhqk,bhkd->bhqd", p, v)
        return torch.einsum("bhqd,hdm->bqm", ctx, w_o)

    def _B_ref(x, w_gate, w_up, w_down):
        g = torch.einsum("bsd,df->bsf", x, w_gate)
        u = torch.einsum("bsd,df->bsf", x, w_up)
        h = _sigmoid(g) * u
        return torch.einsum("bsf,fd->bsd", h, w_down)

    x = A_x
    xn = _layernorm(x, axis=-1)
    return x + _A_ref(xn, A_c_kv, A_w_q, A_w_uk, A_w_uv, A_w_o) + _B_ref(xn, B_w_gate, B_w_up, B_w_down)
```

```cpp
#include <cuda_runtime.h>
#include <cuda_bf16.h>
#include <cuda.h>
#include <stdint.h>

#define DEVI __device__ __forceinline__

namespace mla {

constexpr int NCTA = 128;
constexpr int NTHREADS = 288;
#define TMA_WINDOW 3
constexpr int kPollLimit = 1 << 19;

constexpr uint32_t SM_WQ = 0;
constexpr uint32_t SM_WUK = 32768;
constexpr uint32_t SM_G = 0;
constexpr uint32_t SM_WD = 24576;
constexpr uint32_t SM_SRECV = 36864;
constexpr uint32_t SM_P = 53248;
constexpr uint32_t SM_CKV = 65536;
constexpr uint32_t SM_WUV = 131072;
constexpr uint32_t SM_WO = 163840;
constexpr uint32_t SM_QB = 196608;
constexpr uint32_t SM_ACT = 212992;
constexpr uint32_t ACT_STRIDE = 272;
constexpr uint32_t ACT_X = SM_ACT, ACT_Q = SM_ACT + 1088, ACT_CL = SM_ACT + 2176, ACT_CTX = SM_ACT + 3264,
                   ACT_H = SM_ACT + 4352;
constexpr uint32_t ACT_W = SM_ACT + 5440;
constexpr uint32_t SM_INVL = SM_ACT + 6528;
constexpr uint32_t SM_WMAX = SM_ACT + 6656;
constexpr uint32_t SM_WSUM = SM_WMAX + 1024;
constexpr uint32_t SM_QST = SM_WSUM + 1024;
constexpr uint32_t SM_BAR = SM_QST + 1024;
constexpr uint32_t SM_TL = SM_BAR + 256;
constexpr uint32_t SM_TOTAL = SM_TL + 320;

constexpr int NPIECE = 17;
constexpr int BAR_WQ = 0, BAR_WUK = 2, BAR_CKV = 4, BAR_WUV = 8, BAR_G = 10, BAR_WD = 12, BAR_WO = 13,
              BAR_R1FREE = 17, BAR_S = 18, NBAR = 19;

struct alignas(64) Params {
  CUtensorMap maps[8];
  const __nv_bfloat16* x;
  __nv_bfloat16* out;
  const __nv_bfloat16* wq;
};

struct Scratch {
  uint32_t part[64][2][32][128];
  uint32_t qlat[2][2][32][128];
  float x0[NCTA][256];
  float x2[NCTA][256];
  float x3[4][32][256];
  float xd[NCTA][192];
  float ml[32][64][2];
  uint32_t epoch[NCTA];
};
__device__ Scratch g_scr;

#define TL(i) do {} while (0)
#define TLB(i) do {} while (0)
#define TL_DUMP(a, b) do {} while (0)

DEVI uint32_t smem_u32(const void* p) { return (uint32_t)__cvta_generic_to_shared(p); }
DEVI void mbar_init(uint32_t bar, uint32_t cnt) { asm volatile("mbarrier.init.shared::cta.b64 [%0], %1;" ::"r"(bar), "r"(cnt) : "memory"); }
DEVI void mbar_expect_tx(uint32_t bar, uint32_t bytes) { asm volatile("mbarrier.arrive.expect_tx.shared::cta.b64 _, [%0], %1;" ::"r"(bar), "r"(bytes) : "memory"); }
DEVI void mbar_arrive(uint32_t bar) { asm volatile("mbarrier.arrive.shared::cta.b64 _, [%0];" ::"r"(bar) : "memory"); }
DEVI void mbar_wait(uint32_t bar) {
  asm volatile(
      "{\n.reg .pred p;\n.reg .u32 c;\nmov.u32 c, 0;\n"
      "LAB_WAIT:\n"
      "mbarrier.try_wait.parity.shared::cta.b64 p, [%0], 0;\n"
      "@p bra LAB_DONE;\n"
      "add.u32 c, c, 1;\n"
      "setp.lt.u32 p, c, %1;\n"
      "@p bra LAB_WAIT;\n"
      "trap;\n"
      "LAB_DONE:\n}"
      ::"r"(bar), "n"(kPollLimit) : "memory");
}
DEVI void tma3d(uint32_t dst, const CUtensorMap* tm, int c1, int c2, uint32_t bar) {
  asm volatile("cp.async.bulk.tensor.3d.shared::cluster.global.mbarrier::complete_tx::bytes [%0], [%1, {%3, %4, %5}], [%2];"
               ::"r"(dst), "l"(tm), "r"(bar), "r"(0), "r"(c1), "r"(c2) : "memory");
}
DEVI void prefetch_map(const CUtensorMap* tm) { asm volatile("prefetch.tensormap [%0];" ::"l"(tm) : "memory"); }
DEVI void bar_compute() { asm volatile("bar.sync 1, 256;" ::: "memory"); }
DEVI void fence_async_smem() { asm volatile("fence.proxy.async.shared::cta;" ::: "memory"); }
DEVI void ldsm4(uint32_t (&r)[4], uint32_t addr) {
  asm volatile("ldmatrix.sync.aligned.m8n8.x4.shared.b16 {%0,%1,%2,%3}, [%4];" : "=r"(r[0]), "=r"(r[1]), "=r"(r[2]), "=r"(r[3]) : "r"(addr) : "memory");
}
DEVI void ldsm4t(uint32_t (&r)[4], uint32_t addr) {
  asm volatile("ldmatrix.sync.aligned.m8n8.x4.trans.shared.b16 {%0,%1,%2,%3}, [%4];" : "=r"(r[0]), "=r"(r[1]), "=r"(r[2]), "=r"(r[3]) : "r"(addr) : "memory");
}
DEVI void stsm4t(uint32_t addr, uint32_t r0, uint32_t r1, uint32_t r2, uint32_t r3) {
  asm volatile("stmatrix.sync.aligned.m8n8.x4.trans.shared.b16 [%0], {%1,%2,%3,%4};" ::"r"(addr), "r"(r0), "r"(r1), "r"(r2), "r"(r3) : "memory");
}
DEVI void mma16816(float (&d)[4], const uint32_t (&a)[4], uint32_t b0, uint32_t b1) {
  asm volatile("mma.sync.aligned.m16n8k16.row.col.f32.bf16.bf16.f32 {%0,%1,%2,%3}, {%4,%5,%6,%7}, {%8,%9}, {%0,%1,%2,%3};"
               : "+f"(d[0]), "+f"(d[1]), "+f"(d[2]), "+f"(d[3])
               : "r"(a[0]), "r"(a[1]), "r"(a[2]), "r"(a[3]), "r"(b0), "r"(b1));
}
DEVI uint32_t lds32(uint32_t a) { uint32_t v; asm volatile("ld.shared.u32 %0, [%1];" : "=r"(v) : "r"(a) : "memory"); return v; }
DEVI float lds32f(uint32_t a) { float v; asm volatile("ld.shared.f32 %0, [%1];" : "=f"(v) : "r"(a) : "memory"); return v; }
DEVI float2 lds64f(uint32_t a) { float2 v; asm volatile("ld.shared.v2.f32 {%0,%1}, [%2];" : "=f"(v.x), "=f"(v.y) : "r"(a) : "memory"); return v; }
DEVI uint4 lds128(uint32_t a) { uint4 v; asm volatile("ld.shared.v4.u32 {%0,%1,%2,%3}, [%4];" : "=r"(v.x), "=r"(v.y), "=r"(v.z), "=r"(v.w) : "r"(a) : "memory"); return v; }
DEVI void sts32(uint32_t a, uint32_t v) { asm volatile("st.shared.u32 [%0], %1;" ::"r"(a), "r"(v) : "memory"); }
DEVI void sts32f(uint32_t a, float v) { asm volatile("st.shared.f32 [%0], %1;" ::"r"(a), "f"(v) : "memory"); }
DEVI void sts128(uint32_t a, uint4 v) { asm volatile("st.shared.v4.u32 [%0], {%1,%2,%3,%4};" ::"r"(a), "r"(v.x), "r"(v.y), "r"(v.z), "r"(v.w) : "memory"); }
DEVI void sts128f(uint32_t a, float x, float y, float z, float w) { asm volatile("st.shared.v4.f32 [%0], {%1,%2,%3,%4};" ::"r"(a), "f"(x), "f"(y), "f"(z), "f"(w) : "memory"); }
DEVI uint4 ldg_poll128(const void* p) { uint4 v; asm volatile("ld.relaxed.gpu.global.v4.u32 {%0,%1,%2,%3}, [%4];" : "=r"(v.x), "=r"(v.y), "=r"(v.z), "=r"(v.w) : "l"(p) : "memory"); return v; }
DEVI uint2 ldg_poll64(const void* p) { uint2 v; asm volatile("ld.relaxed.gpu.global.v2.u32 {%0,%1}, [%2];" : "=r"(v.x), "=r"(v.y) : "l"(p) : "memory"); return v; }
DEVI void stg_pub128(void* p, uint4 v) { asm volatile("st.relaxed.gpu.global.v4.u32 [%0], {%1,%2,%3,%4};" ::"l"(p), "r"(v.x), "r"(v.y), "r"(v.z), "r"(v.w) : "memory"); }
DEVI void stg_pub64(void* p, uint32_t x, uint32_t y) { asm volatile("st.relaxed.gpu.global.v2.u32 [%0], {%1,%2};" ::"l"(p), "r"(x), "r"(y) : "memory"); }
DEVI void stg_pub32(void* p, uint32_t x) { asm volatile("st.relaxed.gpu.global.u32 [%0], %1;" ::"l"(p), "r"(x) : "memory"); }
DEVI float ex2(float x) { float y; asm("ex2.approx.ftz.f32 %0, %1;" : "=f"(y) : "f"(x)); return y; }
DEVI uint32_t pack_bf16(float lo, float hi) { uint32_t r; asm("cvt.rn.bf16x2.f32 %0, %1, %2;" : "=r"(r) : "f"(hi), "f"(lo)); return r; }
DEVI float bf_lo(uint32_t w) { return __uint_as_float(w << 16); }
DEVI float bf_hi(uint32_t w) { return __uint_as_float(w & 0xffff0000u); }
DEVI float round15(float v) { uint32_t u = __float_as_uint(v); u = (u + 0xffffu + ((u >> 17) & 1u)) & 0xfffe0000u; return __uint_as_float(u); }
DEVI uint32_t tagf(float v, uint32_t par) { return (__float_as_uint(v) & ~1u) | par; }
DEVI float untagf(uint32_t u) { return __uint_as_float(u & ~1u); }
DEVI bool ok4(const uint4& v, uint32_t npar) { return (((v.x ^ npar) & (v.y ^ npar) & (v.z ^ npar) & (v.w ^ npar)) & 1u) != 0; }
DEVI bool ok2(const uint2& v, uint32_t npar) { return (((v.x ^ npar) & (v.y ^ npar)) & 1u) != 0; }

DEVI uint64_t make_desc(uint32_t addr) {
  return (uint64_t)((addr & 0x3ffffu) >> 4) | (1ull << 16) | (64ull << 32) | (1ull << 62);
}
template <int TA>
DEVI void wgmma_n32(float (&d)[16], uint64_t da, uint64_t db) {
  asm volatile(
      "wgmma.mma_async.sync.aligned.m64n32k16.f32.bf16.bf16 "
      "{%0,%1,%2,%3,%4,%5,%6,%7,%8,%9,%10,%11,%12,%13,%14,%15}, %16, %17, 1, 1, 1, %18, 0;\n"
      : "+f"(d[0]), "+f"(d[1]), "+f"(d[2]), "+f"(d[3]), "+f"(d[4]), "+f"(d[5]), "+f"(d[6]), "+f"(d[7]), "+f"(d[8]),
        "+f"(d[9]), "+f"(d[10]), "+f"(d[11]), "+f"(d[12]), "+f"(d[13]), "+f"(d[14]), "+f"(d[15])
      : "l"(da), "l"(db), "n"(TA));
}
DEVI void fence_regs(float (&d)[16]) {
#pragma unroll
  for (int i = 0; i < 16; i++) asm volatile("" : "+f"(d[i])::"memory");
}
DEVI void wgmma_fence() { asm volatile("wgmma.fence.sync.aligned;" ::: "memory"); }
DEVI void wgmma_commit() { asm volatile("wgmma.commit_group.sync.aligned;" ::: "memory"); }
DEVI void wgmma_wait0() { asm volatile("wgmma.wait_group.sync.aligned 0;" ::: "memory"); }

DEVI void act_store_pair(uint32_t act, int b, int k, float v0, float v1) {
  uint32_t hi = pack_bf16(v0, v1);
  uint32_t lo = pack_bf16(v0 - bf_lo(hi), v1 - bf_hi(hi));
  sts32(act + b * ACT_STRIDE + k * 2, hi);
  sts32(act + (2 + b) * ACT_STRIDE + k * 2, lo);
}

DEVI void gather4(const float* base, uint32_t act, float scale, uint32_t npar, int tid) {
  if (tid < 64) {
    uint4 v[4];
    bool ok[4] = {false, false, false, false};
    int it = 0;
    while (true) {
#pragma unroll
      for (int q = 0; q < 4; q++) if (!ok[q]) v[q] = ldg_poll128(base + q * 256 + tid * 4);
#pragma unroll
      for (int q = 0; q < 4; q++) ok[q] = ok4(v[q], npar);
      if (ok[0] && ok[1] && ok[2] && ok[3]) break;
      if (++it > kPollLimit) __trap();
    }
    float s0 = 0.f, s1 = 0.f, s2 = 0.f, s3 = 0.f;
#pragma unroll
    for (int q = 0; q < 4; q++) { s0 += untagf(v[q].x); s1 += untagf(v[q].y); s2 += untagf(v[q].z); s3 += untagf(v[q].w); }
    act_store_pair(act, 0, 2 * tid, s0 * scale, s2 * scale);
    act_store_pair(act, 1, 2 * tid, s1 * scale, s3 * scale);
  }
}

DEVI void sts16(uint32_t a, uint32_t v) { asm volatile("st.shared.u16 [%0], %1;" ::"r"(a), "h"((uint16_t)v) : "memory"); }
DEVI void prefetch_l2(const void* p) { asm volatile("prefetch.global.L2 [%0];" ::"l"(p)); }

DEVI void issue_piece(int p, const Params& P, uint32_t sm, int h, int j, int cta) {
  const uint32_t b = sm + SM_BAR + 8u * p;
  if (p < 2)        { mbar_expect_tx(b, 16384); tma3d(sm + SM_WQ + p * 16384, &P.maps[0], 128 * j + 64 * p, 2 * h, b); }
  else if (p < 4)   { mbar_expect_tx(b, 16384); tma3d(sm + SM_WUK + (p - 2) * 16384, &P.maps[1], 128 * j + 64 * (p - 2), 2 * h, b); }
  else if (p < 8)   { mbar_expect_tx(b, 16384); tma3d(sm + SM_CKV + (p - 4) * 16384, &P.maps[2], 128 * (cta >> 1) + 64 * ((p - 4) >> 1), 4 * (cta & 1) + 2 * ((p - 4) & 1), b); }
  else if (p < 10)  { mbar_expect_tx(b, 16384); tma3d(sm + SM_WUV + (p - 8) * 16384, &P.maps[3], 128 * j + 64 * (p - 8), 2 * h, b); }
  else if (p < 12)  { mbar_expect_tx(b, 12288); tma3d(sm + SM_G + (p - 10) * 12288, &P.maps[p - 6], 128 * j, 3 * h, b); }
  else if (p == 12) { mbar_expect_tx(b, 12288); tma3d(sm + SM_WD, &P.maps[6], 48 * h, 2 * j, b); }
  else              { mbar_expect_tx(b, 8192); tma3d(sm + SM_WO + (p - 13) * 8192, &P.maps[7], 128 * h + 32 * (p - 13), 2 * j, b); }
}

__global__ void __cluster_dims__(2, 1, 1) __launch_bounds__(NTHREADS, 1)
fused_kernel(const __grid_constant__ Params P) {
  extern __shared__ __align__(1024) uint8_t smem_raw[];
  uint32_t sm = smem_u32(smem_raw);
  int tid = threadIdx.x, cta = blockIdx.x;
  if (tid == 256) {
    prefetch_map(&P.maps[0]);
    prefetch_map(&P.maps[1]);
#pragma unroll
    for (int i = 0; i < TMA_WINDOW; i++) mbar_init(sm + SM_BAR + 8u * i, 1);
#pragma unroll
    for (int p = 0; p < TMA_WINDOW; p++) issue_piece(p, P, sm, cta >> 2, cta & 3, cta);
    TL(16);
    prefetch_map(&P.maps[2]);
#pragma unroll
    for (int i = TMA_WINDOW; i < NBAR; i++) mbar_init(sm + SM_BAR + 8u * i, i == BAR_R1FREE ? 8 : 1);
    asm volatile("fence.mbarrier_init.release.cluster;" ::: "memory");
    mbar_expect_tx(sm + SM_BAR + 8u * BAR_S, 16384);
  }
  asm volatile("" : "+r"(sm), "+r"(tid), "+r"(cta));
  Scratch* Gp = &g_scr;
  asm volatile("" : "+l"(Gp));
  Scratch& G = *Gp;
  const int lane = tid & 31;
  const int warp = __shfl_sync(0xffffffffu, tid >> 5, 0);
  const int h = cta >> 2, j = cta & 3;
  const int pair = cta >> 1, rank = cta & 1;
  auto bar = [&](int i) { return sm + SM_BAR + 8u * i; };

  if (warp == 8) {
    __syncwarp();
    asm volatile("bar.arrive 2, 288;" ::: "memory");
    asm volatile("barrier.cluster.arrive.relaxed.aligned;" ::: "memory");
    const uint32_t epoch = G.epoch[cta];
    const int oq = ((lane >> 4) & 1) * 4 + ((lane >> 3) & 1) * 2 + ((lane >> 2) & 1);
    const int oidx = (h >> 4) * 512 + 128 * j + (h & 15) * 8 + oq;
    const float xres = __bfloat162float(P.x[oidx]);
    if (lane == 0) {
      prefetch_map(&P.maps[3]); prefetch_map(&P.maps[4]); prefetch_map(&P.maps[5]); prefetch_map(&P.maps[6]); prefetch_map(&P.maps[7]);
#pragma unroll
      for (int p = TMA_WINDOW; p < NPIECE; p++) {
        mbar_wait(bar(p - TMA_WINDOW));
        if (p == BAR_G) mbar_wait(bar(BAR_R1FREE));
        issue_piece(p, P, sm, h, j, cta);
        TL(17 + p);
      }
    }
    __syncwarp();
    const uint32_t npar = epoch & 1u;
    const float* src = &G.x3[j][lane][8 * h];
    uint4 a, b;
    int it = 0;
    mbar_wait(bar(NPIECE - 1));
    while (true) {
      a = ldg_poll128(src);
      b = ldg_poll128(src + 4);
      if (__all_sync(0xffffffffu, ok4(a, npar) && ok4(b, npar))) break;
      if (++it > kPollLimit) __trap();
    }
    TL(34);
    float v[8] = {untagf(a.x), untagf(a.y), untagf(a.z), untagf(a.w), untagf(b.x), untagf(b.y), untagf(b.z), untagf(b.w)};
    {
      const bool up = lane & 16;
#pragma unroll
      for (int q = 0; q < 4; q++) { float s = up ? v[q] : v[q + 4], k = up ? v[q + 4] : v[q]; v[q] = k + __shfl_xor_sync(0xffffffffu, s, 16); }
    }
    {
      const bool up = lane & 8;
#pragma unroll
      for (int q = 0; q < 2; q++) { float s = up ? v[q] : v[q + 2], k = up ? v[q + 2] : v[q]; v[q] = k + __shfl_xor_sync(0xffffffffu, s, 8); }
    }
    {
      const bool up = lane & 4;
      float s = up ? v[0] : v[1], k = up ? v[1] : v[0];
      v[0] = k + __shfl_xor_sync(0xffffffffu, s, 4);
    }
    v[0] += __shfl_xor_sync(0xffffffffu, v[0], 2);
    v[0] += __shfl_xor_sync(0xffffffffu, v[0], 1);
    if ((lane & 3) == 0) P.out[oidx] = __float2bfloat16(xres + v[0]);
    if (lane == 0) G.epoch[cta] = epoch + 1;
    TL(35);
    TL_DUMP(16, 36);
    return;
  }

  const int g = lane >> 2, t = lane & 3;
  const uint32_t epoch = G.epoch[cta];

  {
    const int b = warp >> 2, p = tid & 127;
    const uint4* xp = reinterpret_cast<const uint4*>(P.x + b * 512 + lane * 16);
    const uint4 u0 = __ldg(xp), u1 = __ldg(xp + 1);
    const uint32_t xw = __ldg(reinterpret_cast<const uint32_t*>(P.x + b * 512 + 128 * j + 2 * (p & 63)));
    const uint32_t w[8] = {u0.x, u0.y, u0.z, u0.w, u1.x, u1.y, u1.z, u1.w};
    float s = 0.f;
#pragma unroll
    for (int q = 0; q < 8; q++) s += bf_lo(w[q]) + bf_hi(w[q]);
#pragma unroll
    for (int o = 16; o > 0; o >>= 1) s += __shfl_xor_sync(0xffffffffu, s, o);
    const float m = s * (1.f / 512.f);
    float ss = 0.f;
#pragma unroll
    for (int q = 0; q < 8; q++) { float d0 = bf_lo(w[q]) - m, d1 = bf_hi(w[q]) - m; ss += d0 * d0 + d1 * d1; }
#pragma unroll
    for (int o = 16; o > 0; o >>= 1) ss += __shfl_xor_sync(0xffffffffu, ss, o);
    const float r = 1.f / sqrtf(ss * (1.f / 512.f) + 1e-5f);
    if (p < 64) act_store_pair(sm + ACT_X, b, 2 * p, (bf_lo(xw) - m) * r, (bf_hi(xw) - m) * r);
  }
  TL(0);
  const uint32_t par = (epoch + 1u) & 1u, npar = par ^ 1u;
  {
    const uint4 inv = make_uint4(npar, npar, npar, npar);
    uint4* pp = reinterpret_cast<uint4*>(&G.part[pair][rank][0][0]);
#pragma unroll
    for (int i = 0; i < 4; i++) stg_pub128(pp + tid + 256 * i, inv);
    if (tid < 64) stg_pub128(reinterpret_cast<uint4*>(&G.x0[cta][0]) + tid, inv);
    else if (tid < 128) stg_pub128(reinterpret_cast<uint4*>(&G.x2[cta][0]) + (tid - 64), inv);
    else if (tid < 192) stg_pub128(reinterpret_cast<uint4*>(&G.x3[j][h][0]) + (tid - 128), inv);
    else if (tid < 240) stg_pub128(reinterpret_cast<uint4*>(&G.xd[cta][0]) + (tid - 192), inv);
    if (tid < 32) {
      stg_pub128(reinterpret_cast<uint4*>(&G.qlat[tid >> 4][j >> 1][h][(j & 1) * 64]) + (tid & 15), inv);
      if (rank == 0) stg_pub64(&G.ml[tid][pair][0], npar, npar);
    }
  }
  TL(1);
  asm volatile("bar.sync 2, 288;" ::: "memory");
  TLB(2);

  const int mat = lane >> 3, l7 = lane & 7;
  const int tr_row = l7 + (mat >> 1) * 8;
  const uint32_t tr_off = tr_row * 128 + ((((warp & 3) * 2 + (mat & 1)) ^ l7) << 4);
  const uint32_t tr_cb = warp >> 2;
  const uint32_t bf_off = sm + (l7 & 3) * ACT_STRIDE + mat * 16;

  float r0, r1, r2, r3;
  auto reduce_hilo = [&](const float (&d)[4], const float (&e)[4]) {
    r0 = d[0] + e[0]; r1 = d[1] + e[1]; r2 = d[2] + e[2]; r3 = d[3] + e[3];
    r0 += __shfl_xor_sync(0xffffffffu, r0, 1);
    r1 += __shfl_xor_sync(0xffffffffu, r1, 1);
    r2 += __shfl_xor_sync(0xffffffffu, r2, 1);
    r3 += __shfl_xor_sync(0xffffffffu, r3, 1);
  };
  auto gemv_t128 = [&](uint32_t tile, uint32_t act, int bar0) {
    float d[4] = {0.f, 0.f, 0.f, 0.f}, e[4] = {0.f, 0.f, 0.f, 0.f};
    uint32_t b[4][4];
#pragma unroll
    for (int q = 0; q < 4; q++) ldsm4(b[q], bf_off + act + 64 * q);
#pragma unroll
    for (int p = 0; p < 2; p++) {
      mbar_wait(bar(bar0 + p));
      uint32_t a[4][4];
#pragma unroll
      for (int s = 0; s < 4; s++) ldsm4t(a[s], sm + tile + p * 16384 + tr_cb * 8192 + tr_off + s * 2048);
      mma16816(d, a[0], b[2 * p][0], b[2 * p][1]);
      mma16816(e, a[1], b[2 * p][2], b[2 * p][3]);
      mma16816(d, a[2], b[2 * p + 1][0], b[2 * p + 1][1]);
      mma16816(e, a[3], b[2 * p + 1][2], b[2 * p + 1][3]);
    }
    reduce_hilo(d, e);
  };
  auto publish_db = [&](float* dst) {
    if (t == 0) {
      stg_pub64(dst + (16 * warp + g) * 2, tagf(r0, par), tagf(r1, par));
      stg_pub64(dst + (16 * warp + g + 8) * 2, tagf(r2, par), tagf(r3, par));
    }
  };

  gemv_t128(SM_WQ, ACT_X, BAR_WQ);
  publish_db(&G.x0[cta][0]);
  TL(3);
  mbar_wait(bar(BAR_WUK));
  gather4(&G.x0[4 * h][0], sm + ACT_Q, 0.08838834764831845f * 1.4426950408889634f, npar, tid);
  bar_compute();
  TLB(4);
  {
    float d[4] = {0.f, 0.f, 0.f, 0.f}, e[4] = {0.f, 0.f, 0.f, 0.f};
    const int piece = warp >> 2;
    const int row = (warp & 3) * 16 + l7 + (mat & 1) * 8;
    uint32_t b[4][4], a[8][4];
#pragma unroll
    for (int q = 0; q < 4; q++) ldsm4(b[q], bf_off + ACT_Q + 64 * q);
    mbar_wait(bar(BAR_WUK + piece));
#pragma unroll
    for (int s = 0; s < 8; s++) {
      const int chunk = (s & 3) * 2 + (mat >> 1);
      ldsm4(a[s], sm + SM_WUK + piece * 16384 + (s >> 2) * 8192 + row * 128 + ((chunk ^ l7) << 4));
    }
#pragma unroll
    for (int q = 0; q < 4; q++) {
      mma16816(d, a[2 * q], b[q][0], b[q][1]);
      mma16816(e, a[2 * q + 1], b[q][2], b[q][3]);
    }
    reduce_hilo(d, e);
    if (t == 0) {
      sts32f(sm + SM_QST + (16 * warp + g) * 4, r0);
      sts32f(sm + SM_QST + 512 + (16 * warp + g) * 4, r1);
      sts32f(sm + SM_QST + (16 * warp + g + 8) * 4, r2);
      sts32f(sm + SM_QST + 512 + (16 * warp + g + 8) * 4, r3);
    }
    __syncwarp();
    if (lane == 0) mbar_arrive(bar(BAR_R1FREE));
    asm volatile("barrier.cluster.arrive.relaxed.aligned;" ::: "memory");
    bar_compute();
    if (tid < 128) {
      const int b2 = tid >> 6, p = tid & 63;
      float2 v = lds64f(sm + SM_QST + b2 * 512 + p * 8);
      stg_pub32(&G.qlat[b2][j >> 1][h][(j & 1) * 64 + p], pack_bf16(round15(v.x), v.y) | par);
    }
  }
  TL(5);
  {
    mbar_wait(bar(BAR_CKV));
    const int b = pair >> 5;
    const uint4* src = reinterpret_cast<const uint4*>(&G.qlat[b][rank][0][0]);
    uint4 v[4];
    bool ok[4] = {false, false, false, false};
    int it = 0;
    while (true) {
#pragma unroll
      for (int i = 0; i < 4; i++) if (!ok[i]) v[i] = ldg_poll128(src + tid + 256 * i);
#pragma unroll
      for (int i = 0; i < 4; i++) ok[i] = ok4(v[i], npar);
      if (ok[0] && ok[1] && ok[2] && ok[3]) break;
      if (++it > kPollLimit) __trap();
    }
#pragma unroll
    for (int i = 0; i < 4; i++) {
      const int vi = tid + 256 * i, hh = vi >> 5, pc = vi & 31;
      uint4 w = make_uint4(v[i].x & ~1u, v[i].y & ~1u, v[i].z & ~1u, v[i].w & ~1u);
      sts128(sm + SM_QB + (pc >> 3) * 4096 + hh * 128 + (((pc & 7) ^ (hh & 7)) << 4), w);
    }
    fence_async_smem();
    bar_compute();
  }
  TLB(6);
  const int wg = warp >> 2, wq4 = warp & 3;
  float s[16];
#pragma unroll
  for (int i = 0; i < 16; i++) s[i] = 0.f;
  fence_regs(s);
  {
    const uint64_t da = make_desc(sm + SM_CKV + wg * 32768), db = make_desc(sm + SM_QB);
#pragma unroll
    for (int cp = 0; cp < 2; cp++) {
      mbar_wait(bar(BAR_CKV + wg * 2 + cp));
      wgmma_fence();
#pragma unroll
      for (int k = 0; k < 8; k++) {
        const int cb = cp * 2 + (k >> 2), ks = k & 3;
        wgmma_n32<0>(s, da + ((cb * 8192 + ks * 32) >> 4), db + ((cb * 4096 + ks * 32) >> 4));
      }
      wgmma_commit();
    }
  }
  asm volatile("barrier.cluster.wait.aligned;" ::: "memory");
  uint32_t rdst, rbar;
  asm volatile("mapa.shared::cluster.u32 %0, %1, %2;" : "=r"(rdst) : "r"(sm + SM_SRECV + tid * 16), "r"(rank ^ 1));
  asm volatile("mapa.shared::cluster.u32 %0, %1, %2;" : "=r"(rbar) : "r"(bar(BAR_S)), "r"(rank ^ 1));
  wgmma_wait0();
  fence_regs(s);
  TL(7);
  {
#pragma unroll
    for (int q = 0; q < 4; q++)
      asm volatile("st.async.weak.shared::cluster.mbarrier::complete_tx::bytes.v4.f32 [%0], {%1,%2,%3,%4}, [%5];"
                   ::"r"(rdst + q * 4096), "f"(s[4 * q]), "f"(s[4 * q + 1]), "f"(s[4 * q + 2]), "f"(s[4 * q + 3]), "r"(rbar) : "memory");
    mbar_wait(bar(BAR_S));
#pragma unroll
    for (int q = 0; q < 4; q++) {
      uint4 o = lds128(sm + SM_SRECV + tid * 16 + q * 4096);
      s[4 * q] += __uint_as_float(o.x); s[4 * q + 1] += __uint_as_float(o.y);
      s[4 * q + 2] += __uint_as_float(o.z); s[4 * q + 3] += __uint_as_float(o.w);
    }
  }
  TL(8);
  const int mycol = ((lane >> 3) & 3) * 8 + (lane & 3) * 2 + ((lane >> 2) & 1);
  float colmax;
  {
    float v[8];
#pragma unroll
    for (int i = 0; i < 4; i++) { v[2 * i] = fmaxf(s[4 * i], s[4 * i + 2]); v[2 * i + 1] = fmaxf(s[4 * i + 1], s[4 * i + 3]); }
    { const bool up = lane & 16;
#pragma unroll
      for (int q = 0; q < 4; q++) { float a = up ? v[q] : v[q + 4], k = up ? v[q + 4] : v[q]; v[q] = fmaxf(k, __shfl_xor_sync(0xffffffffu, a, 16)); } }
    { const bool up = lane & 8;
#pragma unroll
      for (int q = 0; q < 2; q++) { float a = up ? v[q] : v[q + 2], k = up ? v[q + 2] : v[q]; v[q] = fmaxf(k, __shfl_xor_sync(0xffffffffu, a, 8)); } }
    { const bool up = lane & 4; float a = up ? v[0] : v[1], k = up ? v[1] : v[0]; v[0] = fmaxf(k, __shfl_xor_sync(0xffffffffu, a, 4)); }
    sts32f(sm + SM_WMAX + warp * 128 + mycol * 4, v[0]);
    bar_compute();
    float m = lds32f(sm + SM_WMAX + mycol * 4);
#pragma unroll
    for (int w = 1; w < 8; w++) m = fmaxf(m, lds32f(sm + SM_WMAX + w * 128 + mycol * 4));
    colmax = m;
#pragma unroll
    for (int i = 0; i < 4; i++) {
      const float m0 = __shfl_sync(0xffffffffu, m, (i << 3) | t), m1 = __shfl_sync(0xffffffffu, m, (i << 3) | 4 | t);
      s[4 * i] = ex2(s[4 * i] - m0); s[4 * i + 1] = ex2(s[4 * i + 1] - m1);
      s[4 * i + 2] = ex2(s[4 * i + 2] - m0); s[4 * i + 3] = ex2(s[4 * i + 3] - m1);
    }
#pragma unroll
    for (int c2 = 0; c2 < 2; c2++) {
      const int i = 2 * c2 + (mat >> 1), hh = 8 * i + l7, kc = wq4 * 2 + (mat & 1);
      stsm4t(sm + SM_P + wg * 4096 + hh * 128 + ((kc ^ l7) << 4),
             pack_bf16(s[8 * c2], s[8 * c2 + 1]), pack_bf16(s[8 * c2 + 2], s[8 * c2 + 3]),
             pack_bf16(s[8 * c2 + 4], s[8 * c2 + 5]), pack_bf16(s[8 * c2 + 6], s[8 * c2 + 7]));
    }
    fence_async_smem();
    bar_compute();
  }
  TLB(9);
  {
    float o[2][16];
#pragma unroll
    for (int i = 0; i < 16; i++) { o[0][i] = 0.f; o[1][i] = 0.f; }
    fence_regs(o[0]);
    fence_regs(o[1]);
    const uint64_t da = make_desc(sm + SM_CKV + 2 * wg * 8192), db = make_desc(sm + SM_P);
    wgmma_fence();
#pragma unroll
    for (int k = 0; k < 8; k++) {
      const int kh = k >> 2, ks = k & 3;
#pragma unroll
      for (int mt = 0; mt < 2; mt++)
        wgmma_n32<1>(o[mt], da + ((kh * 32768 + mt * 8192 + ks * 2048) >> 4), db + ((kh * 4096 + ks * 32) >> 4));
    }
    wgmma_commit();
    {
      float v[8];
#pragma unroll
      for (int i = 0; i < 4; i++) { v[2 * i] = s[4 * i] + s[4 * i + 2]; v[2 * i + 1] = s[4 * i + 1] + s[4 * i + 3]; }
      { const bool up = lane & 16;
#pragma unroll
        for (int q = 0; q < 4; q++) { float a = up ? v[q] : v[q + 4], k = up ? v[q + 4] : v[q]; v[q] = k + __shfl_xor_sync(0xffffffffu, a, 16); } }
      { const bool up = lane & 8;
#pragma unroll
        for (int q = 0; q < 2; q++) { float a = up ? v[q] : v[q + 2], k = up ? v[q + 2] : v[q]; v[q] = k + __shfl_xor_sync(0xffffffffu, a, 8); } }
      { const bool up = lane & 4; float a = up ? v[0] : v[1], k = up ? v[1] : v[0]; v[0] = k + __shfl_xor_sync(0xffffffffu, a, 4); }
      sts32f(sm + SM_WSUM + warp * 128 + mycol * 4, v[0]);
    }
    wgmma_wait0();
    fence_regs(o[0]);
    fence_regs(o[1]);
    TL(10);
    const bool even = (g & 1) == 0;
#pragma unroll
    for (int mt = 0; mt < 2; mt++) {
#pragma unroll
      for (int c2 = 0; c2 < 2; c2++) {
        const int i = 2 * c2 + (mat >> 1), hh = 8 * i + l7, cc = (2 * wg + mt) * 8 + wq4 * 2 + (mat & 1);
        uint32_t pk[4];
#pragma unroll
        for (int q = 0; q < 4; q++) {
          float a = o[mt][8 * c2 + 2 * q], bq = o[mt][8 * c2 + 2 * q + 1];
          if (even) { a = round15(a); bq = round15(bq); }
          pk[q] = pack_bf16(a, bq);
        }
        stsm4t(sm + SM_QB + hh * 512 + ((cc ^ l7) << 4), pk[0], pk[1], pk[2], pk[3]);
      }
    }
    bar_compute();
    uint4* dst = reinterpret_cast<uint4*>(&G.part[pair][rank][0][0]);
#pragma unroll
    for (int i = 0; i < 4; i++) {
      const int vi = tid + 256 * i, hh = vi >> 5, cc = vi & 31;
      uint4 w = lds128(sm + SM_QB + hh * 512 + ((cc ^ (hh & 7)) << 4));
      w.x |= par; w.y |= par; w.z |= par; w.w |= par;
      stg_pub128(dst + vi, w);
    }
    if (warp == 7 && rank == 0) {
      float l = lds32f(sm + SM_WSUM + mycol * 4);
#pragma unroll
      for (int w = 1; w < 8; w++) l += lds32f(sm + SM_WSUM + w * 128 + mycol * 4);
      stg_pub64(&G.ml[mycol][pair][0], tagf(colmax, par), tagf(l, par));
    }
  }
  TL(11);
  {
    const int rg = tid >> 4, pc = tid & 15, rk = j >> 1;
    uint4 v[4];
    uint2 ml = make_uint2(par, par);
    bool ok[4] = {false, false, false, false}, okm = warp >= 2;
    int it = 0;
    while (true) {
#pragma unroll
      for (int i = 0; i < 4; i++)
        if (!ok[i]) v[i] = ldg_poll128(&G.part[16 * i + rg][rk][h][(j & 1) * 64 + pc * 4]);
      if (!okm) ml = ldg_poll64(&G.ml[h][tid][0]);
      okm = ok2(ml, npar);
#pragma unroll
      for (int i = 0; i < 4; i++) ok[i] = ok4(v[i], npar);
      if (__all_sync(0xffffffffu, okm && ok[0] && ok[1] && ok[2] && ok[3])) break;
      if (++it > kPollLimit) __trap();
    }
    TL(12);
    float el = 0.f;
    if (warp < 2) {
      const float m = untagf(ml.x);
      float mx = m;
#pragma unroll
      for (int o = 16; o > 0; o >>= 1) mx = fmaxf(mx, __shfl_xor_sync(0xffffffffu, mx, o));
      const float e = ex2(m - mx);
      el = e * untagf(ml.y);
      const uint32_t hi = pack_bf16(e, 0.f) & 0xffffu, lo = pack_bf16(e - bf_lo(hi), 0.f) & 0xffffu;
      const uint32_t a = sm + ACT_W + tid * 2;
      sts16(a + warp * ACT_STRIDE, hi);
      sts16(a + (2 + warp) * ACT_STRIDE, lo);
      sts16(a + (1 - warp) * ACT_STRIDE, 0);
      sts16(a + (3 - warp) * ACT_STRIDE, 0);
    }
#pragma unroll
    for (int i = 0; i < 4; i++) {
      const int k = 16 * i + rg;
      uint4 w = make_uint4(v[i].x & ~1u, v[i].y & ~1u, v[i].z & ~1u, v[i].w & ~1u);
      sts128(sm + SM_CKV + (pc >> 3) * 8192 + k * 128 + (((pc & 7) ^ (k & 7)) << 4), w);
    }
    bar_compute();
    if (warp < 2) {
#pragma unroll
      for (int o = 16; o > 0; o >>= 1) el += __shfl_xor_sync(0xffffffffu, el, o);
      if (lane == 0) sts32f(sm + SM_INVL + warp * 4, 1.f / el);
    }
    float d[4] = {0.f, 0.f, 0.f, 0.f}, e[4] = {0.f, 0.f, 0.f, 0.f};
    uint32_t b[2][4], a[4][4];
    ldsm4(b[0], bf_off + ACT_W);
    ldsm4(b[1], bf_off + ACT_W + 64);
#pragma unroll
    for (int s4 = 0; s4 < 4; s4++) ldsm4t(a[s4], sm + SM_CKV + tr_cb * 8192 + tr_off + s4 * 2048);
    mma16816(d, a[0], b[0][0], b[0][1]);
    mma16816(e, a[1], b[0][2], b[0][3]);
    mma16816(d, a[2], b[1][0], b[1][1]);
    mma16816(e, a[3], b[1][2], b[1][3]);
    reduce_hilo(d, e);
    {
      const float val = (t & 2) ? ((t & 1) ? r3 : r2) : ((t & 1) ? r1 : r0);
      const uint32_t hi = pack_bf16(val, 0.f) & 0xffffu, lo = pack_bf16(val - bf_lo(hi), 0.f) & 0xffffu;
      const uint32_t a2 = sm + ACT_CL + (t & 1) * ACT_STRIDE + (16 * warp + g + 8 * (t >> 1)) * 2;
      sts16(a2, hi);
      sts16(a2 + 2 * ACT_STRIDE, lo);
    }
    bar_compute();
  }
  TLB(13);
  {
    gemv_t128(SM_WUV, ACT_CL, BAR_WUV);
    const float2 il = lds64f(sm + SM_INVL);
    r0 *= il.x; r1 *= il.y; r2 *= il.x; r3 *= il.y;
    publish_db(&G.x2[cta][0]);
  }
  TL(14);
  if (warp < 6) {
    const int m2 = warp >= 3, tile = warp - 3 * m2;
    float d[4] = {0.f, 0.f, 0.f, 0.f}, e[4] = {0.f, 0.f, 0.f, 0.f};
    uint32_t a[8][4], b[4][4];
#pragma unroll
    for (int q = 0; q < 4; q++) ldsm4(b[q], bf_off + ACT_X + 64 * q);
    mbar_wait(bar(BAR_G + m2));
    const uint32_t abase = sm + SM_G + m2 * 12288 + tile * 4096 + tr_row * 32 + (((mat & 1) ^ ((tr_row >> 2) & 1)) << 4);
#pragma unroll
    for (int s8 = 0; s8 < 8; s8++) ldsm4t(a[s8], abase + s8 * 512);
#pragma unroll
    for (int q = 0; q < 4; q++) {
      mma16816(d, a[2 * q], b[q][0], b[q][1]);
      mma16816(e, a[2 * q + 1], b[q][2], b[q][3]);
    }
    reduce_hilo(d, e);
    publish_db(&G.xd[cta][m2 * 96 + tile * 32] - 32 * warp);
  }
  TL(15);
  gather4(&G.x2[4 * h][0], sm + ACT_CTX, 1.f, npar, tid);
  if (tid >= 64 && tid < 88) {
    const int p = tid - 64;
    uint4 v[8];
    int it = 0;
    while (true) {
      bool ok = true;
#pragma unroll
      for (int q = 0; q < 4; q++) {
        v[2 * q] = ldg_poll128(&G.xd[4 * h + q][p * 4]);
        v[2 * q + 1] = ldg_poll128(&G.xd[4 * h + q][96 + p * 4]);
      }
#pragma unroll
      for (int q = 0; q < 8; q++) ok = ok && ok4(v[q], npar);
      if (ok) break;
      if (++it > kPollLimit) __trap();
    }
    float gg[4] = {0.f, 0.f, 0.f, 0.f}, uu[4] = {0.f, 0.f, 0.f, 0.f};
#pragma unroll
    for (int q = 0; q < 4; q++) {
      gg[0] += untagf(v[2 * q].x); gg[1] += untagf(v[2 * q].y); gg[2] += untagf(v[2 * q].z); gg[3] += untagf(v[2 * q].w);
      uu[0] += untagf(v[2 * q + 1].x); uu[1] += untagf(v[2 * q + 1].y); uu[2] += untagf(v[2 * q + 1].z); uu[3] += untagf(v[2 * q + 1].w);
    }
    float hh[4];
#pragma unroll
    for (int q = 0; q < 4; q++) hh[q] = __fdividef(uu[q], 1.f + __expf(-gg[q]));
    act_store_pair(sm + ACT_H, 0, 2 * p, hh[0], hh[2]);
    act_store_pair(sm + ACT_H, 1, 2 * p, hh[1], hh[3]);
  }
  bar_compute();
  TLB(36);
  {
    float d[4] = {0.f, 0.f, 0.f, 0.f}, e[4] = {0.f, 0.f, 0.f, 0.f};
    uint32_t b[4][4], bh[2][4];
#pragma unroll
    for (int q = 0; q < 4; q++) ldsm4(b[q], bf_off + ACT_CTX + 64 * q);
    ldsm4(bh[0], bf_off + ACT_H);
    ldsm4(bh[1], bf_off + ACT_H + 64);
    mbar_wait(bar(BAR_WD));
    {
      uint32_t a[3][4];
#pragma unroll
      for (int s3 = 0; s3 < 3; s3++) ldsm4t(a[s3], sm + SM_WD + tr_cb * 6144 + tr_off + s3 * 2048);
      mma16816(d, a[0], bh[0][0], bh[0][1]);
      mma16816(e, a[1], bh[0][2], bh[0][3]);
      mma16816(d, a[2], bh[1][0], bh[1][1]);
    }
#pragma unroll
    for (int p = 0; p < 4; p++) {
      mbar_wait(bar(BAR_WO + p));
      uint32_t a0[4], a1[4];
      ldsm4t(a0, sm + SM_WO + p * 8192 + tr_cb * 4096 + tr_off);
      ldsm4t(a1, sm + SM_WO + p * 8192 + tr_cb * 4096 + tr_off + 2048);
      mma16816(d, a0, b[p][0], b[p][1]);
      mma16816(e, a1, b[p][2], b[p][3]);
    }
    reduce_hilo(d, e);
    if (t < 2) {
      float* dst = &G.x3[j][h][t * 128 + 16 * warp + g];
      stg_pub32(dst, tagf(t ? r1 : r0, par));
      stg_pub32(dst + 8, tagf(t ? r3 : r2, par));
    }
  }
  TL(37);
  TL_DUMP(0, 16);
  TL_DUMP(36, 38);
}

typedef CUresult (*EncodeFn)(CUtensorMap*, CUtensorMapDataType, cuuint32_t, void*, const cuuint64_t*, const cuuint64_t*,
                             const cuuint32_t*, const cuuint32_t*, CUtensorMapInterleave, CUtensorMapSwizzle,
                             CUtensorMapL2promotion, CUtensorMapFloatOOBfill);

static void make_map(EncodeFn enc, CUtensorMap* m, const void* base, uint64_t inner, uint64_t rows, uint64_t row_bytes,
                     uint64_t nblk, uint32_t box_rows, uint32_t box_blk, CUtensorMapSwizzle sw) {
  cuuint64_t dims[3] = {inner, rows, nblk};
  cuuint64_t strides[2] = {row_bytes, inner * 2};
  cuuint32_t box[3] = {(cuuint32_t)inner, box_rows, box_blk};
  cuuint32_t es[3] = {1, 1, 1};
  enc(m, CU_TENSOR_MAP_DATA_TYPE_BFLOAT16, 3, const_cast<void*>(base), dims, strides, box, es, CU_TENSOR_MAP_INTERLEAVE_NONE, sw,
      CU_TENSOR_MAP_L2_PROMOTION_L2_128B, CU_TENSOR_MAP_FLOAT_OOB_FILL_NONE);
}

}

extern "C" void kernel_launch(void* const* d_in, const int* in_sizes, int n_in, void* d_out, int out_size) {
  using namespace mla;
  (void)in_sizes; (void)n_in; (void)out_size;
  static EncodeFn enc = nullptr;
  if (!enc) {
    void* fn = nullptr;
    cudaDriverEntryPointQueryResult st;
    cudaGetDriverEntryPoint("cuTensorMapEncodeTiled", &fn, cudaEnableDefault, &st);
    enc = (EncodeFn)fn;
    cudaFuncSetAttribute(fused_kernel, cudaFuncAttributeMaxDynamicSharedMemorySize, (int)SM_TOTAL);
  }
  Params p;
  make_map(enc, &p.maps[0], d_in[2], 64, 512, 8192, 64, 64, 2, CU_TENSOR_MAP_SWIZZLE_128B);
  make_map(enc, &p.maps[1], d_in[3], 64, 512, 8192, 64, 64, 2, CU_TENSOR_MAP_SWIZZLE_128B);
  make_map(enc, &p.maps[3], d_in[4], 64, 512, 8192, 64, 64, 2, CU_TENSOR_MAP_SWIZZLE_128B);
  make_map(enc, &p.maps[2], d_in[1], 64, 8192, 1024, 8, 64, 2, CU_TENSOR_MAP_SWIZZLE_128B);
  make_map(enc, &p.maps[7], d_in[5], 64, 4096, 1024, 8, 32, 2, CU_TENSOR_MAP_SWIZZLE_128B);
  make_map(enc, &p.maps[6], d_in[9], 64, 1376, 1024, 8, 48, 2, CU_TENSOR_MAP_SWIZZLE_128B);
  make_map(enc, &p.maps[4], d_in[7], 16, 512, 2752, 86, 128, 3, CU_TENSOR_MAP_SWIZZLE_32B);
  make_map(enc, &p.maps[5], d_in[8], 16, 512, 2752, 86, 128, 3, CU_TENSOR_MAP_SWIZZLE_32B);
  p.x = (const __nv_bfloat16*)d_in[0];
  p.out = (__nv_bfloat16*)d_out;
  p.wq = (const __nv_bfloat16*)d_in[2];
  fused_kernel<<<NCTA, NTHREADS, SM_TOTAL>>>(p);
}
```

```cpp
#include <cuda_runtime.h>
#include <cuda_bf16.h>
#include <cuda.h>
#include <stdint.h>

#define DEVI __device__ __forceinline__

namespace mla {

constexpr int NCTA = 128;
constexpr int NTHREADS = 320;
constexpr int kPollLimit = 1 << 18;
#define PACE_T0 1000
#define PACE_DT1 169
#define PACE_DT2 169
#define WINDOW 4
#define XQ_PIECE 1
#define PRE_T0 2500
#define PRE_DT 80
#define GAP1 350
#define GAP2 300
#define PAUSE_AT 18
#define PAUSE_NS 550
#define PAUSE2_AT 19
#define PAUSE2_NS 0
#define STAGGER 0
#define X0_PIECE 1
#define X1_DELAY 600
#define X1_DELAY_B 1200
#define X3_DELAY 300
#ifndef M_DELAY
#define M_DELAY 200
#endif
#define PIPE_POLL 0
#define X2_DELAY 300

constexpr uint32_t SM_WQ = 0;
constexpr uint32_t SM_WUK = 32768;
constexpr uint32_t SM_G = 0;
constexpr uint32_t SM_WD = 24576;
constexpr uint32_t SM_SRECV = 36864;
constexpr uint32_t SM_P = 53248;
constexpr uint32_t SM_CKV = 65536;
constexpr uint32_t SM_WUV = 131072;
constexpr uint32_t SM_WO = 163840;
constexpr uint32_t SM_QB = 196608;
constexpr uint32_t SM_ACT = 212992;
constexpr uint32_t ACT_STRIDE = 272;
constexpr uint32_t ACT_X = SM_ACT, ACT_Q = SM_ACT + 1088;
constexpr uint32_t ACT_CL = SM_ACT + 2176, ACT_CTX = ACT_CL + 544, ACT_H = ACT_CTX + 544, ACT_W = ACT_H + 544;
constexpr uint32_t SM_INVL = ACT_W + 544;
constexpr uint32_t SM_WMAX = SM_INVL + 64;
constexpr uint32_t SM_WSUM = SM_WMAX + 1024;
constexpr uint32_t SM_QST = SM_WSUM + 1024;
constexpr uint32_t SM_M0 = SM_QST, SM_M = SM_QST + 128;
constexpr uint32_t SM_BAR = SM_QST + 1024;
constexpr uint32_t SM_TL = SM_BAR + 256;
constexpr uint32_t SM_TOTAL = SM_TL + 320;
static_assert(SM_BAR % 8 == 0 && SM_WMAX % 16 == 0, "alignment");

constexpr int NPIECE = 23;
constexpr int BAR_WUK = 0, BAR_CKV = 4, BAR_G = 12, BAR_WUV = 14, BAR_WD = 18, BAR_WO = 19,
              BAR_R1FREE = 23, BAR_S = 24, NBAR = 26;

struct alignas(64) Maps { CUtensorMap m[7]; };

struct Scratch {
  uint32_t part[64][2][4][32][32];
  uint32_t qlat[2][2][32][128];
  float x0[NCTA][256];
  float x2[NCTA][256];
  float x3[4][32][256];
  float xd[NCTA][192];
  float mx[32][64];
  float ls[32][64];
  uint32_t epoch[NCTA];
};
__device__ Scratch g_scr;

#define TL(i) do {} while (0)
#define TLW(i) do {} while (0)
#define TLB(i) do {} while (0)
#define TLV(i, val) do {} while (0)
#define TL_DUMP(a, b) do {} while (0)

DEVI uint32_t smem_u32(const void* p) { return (uint32_t)__cvta_generic_to_shared(p); }
DEVI void mbar_init(uint32_t bar, uint32_t cnt) { asm volatile("mbarrier.init.shared::cta.b64 [%0], %1;" ::"r"(bar), "r"(cnt) : "memory"); }
DEVI void mbar_expect_tx(uint32_t bar, uint32_t bytes) { asm volatile("mbarrier.arrive.expect_tx.shared::cta.b64 _, [%0], %1;" ::"r"(bar), "r"(bytes) : "memory"); }
DEVI void mbar_arrive(uint32_t bar) { asm volatile("mbarrier.arrive.shared::cta.b64 _, [%0];" ::"r"(bar) : "memory"); }
DEVI void mbar_wait(uint32_t bar) {
  asm volatile(
      "{\n.reg .pred p, q;\n.reg .s32 c;\nmov.s32 c, 16384;\n"
      "LAB_WAIT:\n"
      "mbarrier.try_wait.parity.shared::cta.b64 p, [%0], 0;\n"
      "add.s32 c, c, -1;\n"
      "setp.gt.and.s32 q, c, 0, !p;\n"
      "@q bra LAB_WAIT;\n}"
      ::"r"(bar) : "memory");
}
DEVI void tma4d(uint32_t dst, const void* tm, int c1, int c2, int c3, uint32_t bar) {
  asm volatile("cp.async.bulk.tensor.4d.shared::cluster.global.mbarrier::complete_tx::bytes [%0], [%1, {%3, %4, %5, %6}], [%2];"
               ::"r"(dst), "l"(tm), "r"(bar), "r"(0), "r"(c1), "r"(c2), "r"(c3) : "memory");
}
DEVI void prefetch_map(const void* tm) { asm volatile("prefetch.tensormap [%0];" ::"l"(tm) : "memory"); }
DEVI void bar_compute() { asm volatile("bar.sync 1, 256;" ::: "memory"); }
DEVI void bar_sync(int id, int n) { asm volatile("bar.sync %0, %1;" ::"r"(id), "r"(n) : "memory"); }
DEVI void bar_arrive(int id, int n) { asm volatile("bar.arrive %0, %1;" ::"r"(id), "r"(n) : "memory"); }
DEVI uint32_t gtime() { uint32_t t; asm volatile("mov.u32 %0, %%globaltimer_lo;" : "=r"(t)); return t; }
DEVI void fence_async_smem() { asm volatile("fence.proxy.async.shared::cta;" ::: "memory"); }
DEVI void ldsm4(uint32_t (&r)[4], uint32_t addr) {
  asm volatile("ldmatrix.sync.aligned.m8n8.x4.shared.b16 {%0,%1,%2,%3}, [%4];" : "=r"(r[0]), "=r"(r[1]), "=r"(r[2]), "=r"(r[3]) : "r"(addr) : "memory");
}
DEVI void ldsm4t(uint32_t (&r)[4], uint32_t addr) {
  asm volatile("ldmatrix.sync.aligned.m8n8.x4.trans.shared.b16 {%0,%1,%2,%3}, [%4];" : "=r"(r[0]), "=r"(r[1]), "=r"(r[2]), "=r"(r[3]) : "r"(addr) : "memory");
}
DEVI void stsm4t(uint32_t addr, uint32_t r0, uint32_t r1, uint32_t r2, uint32_t r3) {
  asm volatile("stmatrix.sync.aligned.m8n8.x4.trans.shared.b16 [%0], {%1,%2,%3,%4};" ::"r"(addr), "r"(r0), "r"(r1), "r"(r2), "r"(r3) : "memory");
}
DEVI void mma16816(float (&d)[4], const uint32_t (&a)[4], uint32_t b0, uint32_t b1) {
  asm volatile("mma.sync.aligned.m16n8k16.row.col.f32.bf16.bf16.f32 {%0,%1,%2,%3}, {%4,%5,%6,%7}, {%8,%9}, {%0,%1,%2,%3};"
               : "+f"(d[0]), "+f"(d[1]), "+f"(d[2]), "+f"(d[3])
               : "r"(a[0]), "r"(a[1]), "r"(a[2]), "r"(a[3]), "r"(b0), "r"(b1));
}
DEVI void mma16816z(float (&d)[4], const uint32_t (&a)[4], uint32_t b0, uint32_t b1) {
  asm volatile("mma.sync.aligned.m16n8k16.row.col.f32.bf16.bf16.f32 {%0,%1,%2,%3}, {%4,%5,%6,%7}, {%8,%9}, {%10,%10,%10,%10};"
               : "=f"(d[0]), "=f"(d[1]), "=f"(d[2]), "=f"(d[3])
               : "r"(a[0]), "r"(a[1]), "r"(a[2]), "r"(a[3]), "r"(b0), "r"(b1), "f"(0.f));
}
DEVI uint32_t lds32(uint32_t a) { uint32_t v; asm volatile("ld.shared.u32 %0, [%1];" : "=r"(v) : "r"(a) : "memory"); return v; }
DEVI float lds32f(uint32_t a) { float v; asm volatile("ld.shared.f32 %0, [%1];" : "=f"(v) : "r"(a) : "memory"); return v; }
DEVI float2 lds64f(uint32_t a) { float2 v; asm volatile("ld.shared.v2.f32 {%0,%1}, [%2];" : "=f"(v.x), "=f"(v.y) : "r"(a) : "memory"); return v; }
DEVI uint4 lds128(uint32_t a) { uint4 v; asm volatile("ld.shared.v4.u32 {%0,%1,%2,%3}, [%4];" : "=r"(v.x), "=r"(v.y), "=r"(v.z), "=r"(v.w) : "r"(a) : "memory"); return v; }
DEVI void sts16(uint32_t a, uint32_t v) { asm volatile("st.shared.u16 [%0], %1;" ::"r"(a), "h"((uint16_t)v) : "memory"); }
DEVI void sts32(uint32_t a, uint32_t v) { asm volatile("st.shared.u32 [%0], %1;" ::"r"(a), "r"(v) : "memory"); }
DEVI void sts32f(uint32_t a, float v) { asm volatile("st.shared.f32 [%0], %1;" ::"r"(a), "f"(v) : "memory"); }
DEVI void sts128(uint32_t a, uint4 v) { asm volatile("st.shared.v4.u32 [%0], {%1,%2,%3,%4};" ::"r"(a), "r"(v.x), "r"(v.y), "r"(v.z), "r"(v.w) : "memory"); }
DEVI uint4 ldg_poll128(const void* p) { uint4 v; asm volatile("ld.relaxed.gpu.global.v4.u32 {%0,%1,%2,%3}, [%4];" : "=r"(v.x), "=r"(v.y), "=r"(v.z), "=r"(v.w) : "l"(p) : "memory"); return v; }
DEVI uint32_t ldg_poll32(const void* p) { uint32_t v; asm volatile("ld.relaxed.gpu.global.u32 %0, [%1];" : "=r"(v) : "l"(p) : "memory"); return v; }
DEVI void stg_pub128(void* p, uint4 v) { asm volatile("st.relaxed.gpu.global.v4.u32 [%0], {%1,%2,%3,%4};" ::"l"(p), "r"(v.x), "r"(v.y), "r"(v.z), "r"(v.w) : "memory"); }
DEVI void stg_pub64(void* p, uint32_t x, uint32_t y) { asm volatile("st.relaxed.gpu.global.v2.u32 [%0], {%1,%2};" ::"l"(p), "r"(x), "r"(y) : "memory"); }
DEVI void stg_pub32(void* p, uint32_t x) { asm volatile("st.relaxed.gpu.global.u32 [%0], %1;" ::"l"(p), "r"(x) : "memory"); }
DEVI float ex2(float x) { float y; asm("ex2.approx.ftz.f32 %0, %1;" : "=f"(y) : "f"(x)); return y; }
DEVI uint32_t pack_bf16(float lo, float hi) { uint32_t r; asm("cvt.rn.bf16x2.f32 %0, %1, %2;" : "=r"(r) : "f"(hi), "f"(lo)); return r; }
DEVI float bf_lo(uint32_t w) { return __uint_as_float(w << 16); }
DEVI float bf_hi(uint32_t w) { return __uint_as_float(w & 0xffff0000u); }
DEVI uint32_t tagf(float v, uint32_t par) { return (__float_as_uint(v) & ~1u) | par; }
DEVI float asf(uint32_t u) { return __uint_as_float(u); }
DEVI uint32_t xand(uint32_t a, uint32_t b, uint32_t c) { uint32_t r; asm("lop3.b32 %0, %1, %2, %3, 0x42;" : "=r"(r) : "r"(a), "r"(b), "r"(c)); return r; }
DEVI bool ok4(const uint4& v, uint32_t npar) { return (xand(v.x, v.y, npar) & xand(v.z, v.w, npar) & 1u) != 0; }
DEVI float shx(float v, int m) { return __shfl_xor_sync(0xffffffffu, v, m); }

DEVI uint64_t make_desc(uint32_t addr, uint32_t sbo) {
  return (uint64_t)((addr & 0x3ffffu) >> 4) | (1ull << 16) | ((uint64_t)(sbo >> 4) << 32) | (1ull << 62);
}
template <bool ACC>
DEVI void wgmma_ss(float (&d)[16], uint64_t da, uint64_t db) {
  asm volatile(
      "{\n.reg .pred p;\nsetp.ne.b32 p, %18, 0;\n"
      "wgmma.mma_async.sync.aligned.m64n32k16.f32.bf16.bf16 "
      "{%0,%1,%2,%3,%4,%5,%6,%7,%8,%9,%10,%11,%12,%13,%14,%15}, %16, %17, p, 1, 1, 0, 0;\n}"
      : "+f"(d[0]), "+f"(d[1]), "+f"(d[2]), "+f"(d[3]), "+f"(d[4]), "+f"(d[5]), "+f"(d[6]), "+f"(d[7]), "+f"(d[8]),
        "+f"(d[9]), "+f"(d[10]), "+f"(d[11]), "+f"(d[12]), "+f"(d[13]), "+f"(d[14]), "+f"(d[15])
      : "l"(da), "l"(db), "n"(ACC ? 1 : 0));
}
template <bool ACC>
DEVI void wgmma_rs(float (&d)[16], const uint32_t (&a)[4], uint64_t db) {
  asm volatile(
      "{\n.reg .pred p;\nsetp.ne.b32 p, %21, 0;\n"
      "wgmma.mma_async.sync.aligned.m64n32k16.f32.bf16.bf16 "
      "{%0,%1,%2,%3,%4,%5,%6,%7,%8,%9,%10,%11,%12,%13,%14,%15}, {%16,%17,%18,%19}, %20, p, 1, 1, 0;\n}"
      : "+f"(d[0]), "+f"(d[1]), "+f"(d[2]), "+f"(d[3]), "+f"(d[4]), "+f"(d[5]), "+f"(d[6]), "+f"(d[7]), "+f"(d[8]),
        "+f"(d[9]), "+f"(d[10]), "+f"(d[11]), "+f"(d[12]), "+f"(d[13]), "+f"(d[14]), "+f"(d[15])
      : "r"(a[0]), "r"(a[1]), "r"(a[2]), "r"(a[3]), "l"(db), "n"(ACC ? 1 : 0));
}
DEVI void def_regs(float (&d)[16]) {
#pragma unroll
  for (int i = 0; i < 16; i++) asm volatile("" : "=f"(d[i])::"memory");
}
DEVI void fence_regs(float (&d)[16]) {
#pragma unroll
  for (int i = 0; i < 16; i++) asm volatile("" : "+f"(d[i])::"memory");
}
DEVI void wgmma_fence() { asm volatile("wgmma.fence.sync.aligned;" ::: "memory"); }
DEVI void wgmma_commit() { asm volatile("wgmma.commit_group.sync.aligned;" ::: "memory"); }
template <int N> DEVI void wgmma_wait() { asm volatile("wgmma.wait_group.sync.aligned %0;" ::"n"(N) : "memory"); }

DEVI void act_store_hilo(uint32_t a, float v0, float v1) {
  const uint32_t hi = pack_bf16(v0, v1);
  sts32(a, hi);
  sts32(a + 2 * ACT_STRIDE, pack_bf16(v0 - bf_lo(hi), v1 - bf_hi(hi)));
}
#define POLL_TL_ARGS
#define POLL_TL(tb)
template <int N>
DEVI void poll_issue(uint4 (&v)[N], const char* p, uint32_t stride) {
  static_assert(N == 2 || N == 4, "");
  if constexpr (N == 4) {
    asm volatile(
        "ld.relaxed.gpu.global.v4.u32 {%0,%1,%2,%3}, [%16];\n"
        "ld.relaxed.gpu.global.v4.u32 {%4,%5,%6,%7}, [%17];\n"
        "ld.relaxed.gpu.global.v4.u32 {%8,%9,%10,%11}, [%18];\n"
        "ld.relaxed.gpu.global.v4.u32 {%12,%13,%14,%15}, [%19];"
        : "=r"(v[0].x), "=r"(v[0].y), "=r"(v[0].z), "=r"(v[0].w), "=r"(v[1].x), "=r"(v[1].y), "=r"(v[1].z), "=r"(v[1].w),
          "=r"(v[2].x), "=r"(v[2].y), "=r"(v[2].z), "=r"(v[2].w), "=r"(v[3].x), "=r"(v[3].y), "=r"(v[3].z), "=r"(v[3].w)
        : "l"(p), "l"(p + stride), "l"(p + 2 * stride), "l"(p + 3 * stride) : "memory");
  } else {
    asm volatile(
        "ld.relaxed.gpu.global.v4.u32 {%0,%1,%2,%3}, [%8];\n"
        "ld.relaxed.gpu.global.v4.u32 {%4,%5,%6,%7}, [%9];"
        : "=r"(v[0].x), "=r"(v[0].y), "=r"(v[0].z), "=r"(v[0].w), "=r"(v[1].x), "=r"(v[1].y), "=r"(v[1].z), "=r"(v[1].w)
        : "l"(p), "l"(p + stride) : "memory");
  }
}
DEVI void spin_clk(uint32_t n) {
  uint32_t c0, c;
  asm volatile("mov.u32 %0, %%clock;" : "=r"(c0) :: "memory");
  do { asm volatile("mov.u32 %0, %%clock;" : "=r"(c) :: "memory"); } while (c - c0 < n);
}
template <int N, int GAP>
DEVI void poll_finish(uint4 (&r)[N], const char* p, uint32_t stride, uint32_t npar POLL_TL_ARGS) {
  int it = kPollLimit;
  bool ok[N], all = true;
#pragma unroll
  for (int q = 0; q < N; q++) { ok[q] = ok4(r[q], npar); all = all && ok[q]; }
  if (!PIPE_POLL) {
    while (!all && --it > 0) {
#pragma unroll
      for (int q = 0; q < N; q++) if (!ok[q]) r[q] = ldg_poll128(p + q * stride);
      all = true;
#pragma unroll
      for (int q = 0; q < N; q++) { ok[q] = ok4(r[q], npar); all = all && ok[q]; }
    }
  } else if (!all) {
    uint4 a[N], b[N];
#pragma unroll
    for (int q = 0; q < N; q++) { a[q] = r[q]; b[q] = r[q]; if (!ok[q]) a[q] = ldg_poll128(p + q * stride); }
    spin_clk(GAP);
    do {
#pragma unroll
      for (int q = 0; q < N; q++) if (!ok[q]) b[q] = ldg_poll128(p + q * stride);
      all = true;
#pragma unroll
      for (int q = 0; q < N; q++) { if (!ok[q] && ok4(a[q], npar)) { r[q] = a[q]; ok[q] = true; } all = all && ok[q]; }
      if (all) break;
#pragma unroll
      for (int q = 0; q < N; q++) if (!ok[q]) a[q] = ldg_poll128(p + q * stride);
      all = true;
#pragma unroll
      for (int q = 0; q < N; q++) { if (!ok[q] && ok4(b[q], npar)) { r[q] = b[q]; ok[q] = true; } all = all && ok[q]; }
    } while (!all && --it > 0);
  }
  TL(tb + 2);
  TLV(tb + 3, kPollLimit - it + 1);
}
DEVI void poll_pair(uint32_t& m0, uint32_t& m1, const float* p, uint32_t npar) {
  int it = kPollLimit;
  if (!PIPE_POLL) {
    do { m0 = ldg_poll32(p); m1 = ldg_poll32(p + 32); } while (!__all_sync(0xffffffffu, ((m0 ^ npar) & (m1 ^ npar) & 1u) != 0) && --it > 0);
    return;
  }
  uint32_t a0 = ldg_poll32(p), a1 = ldg_poll32(p + 32), b0, b1;
  spin_clk(GAP2);
  do {
    b0 = ldg_poll32(p); b1 = ldg_poll32(p + 32);
    if (__all_sync(0xffffffffu, ((a0 ^ npar) & (a1 ^ npar) & 1u) != 0)) { m0 = a0; m1 = a1; return; }
    a0 = ldg_poll32(p); a1 = ldg_poll32(p + 32);
    if (__all_sync(0xffffffffu, ((b0 ^ npar) & (b1 ^ npar) & 1u) != 0)) break;
  } while (--it > 0);
  m0 = b0; m1 = b1;
}
template <bool MAX>
DEVI float col_reduce(float (&v)[8], int lane) {
  const bool u16 = lane & 16, u8 = lane & 8, u4 = lane & 4;
#pragma unroll
  for (int q = 0; q < 4; q++) { const float a = u16 ? v[q] : v[q + 4], k = u16 ? v[q + 4] : v[q], o = shx(a, 16); v[q] = MAX ? fmaxf(k, o) : k + o; }
#pragma unroll
  for (int q = 0; q < 2; q++) { const float a = u8 ? v[q] : v[q + 2], k = u8 ? v[q + 2] : v[q], o = shx(a, 8); v[q] = MAX ? fmaxf(k, o) : k + o; }
  const float a = u4 ? v[0] : v[1], k = u4 ? v[1] : v[0], o = shx(a, 4);
  return MAX ? fmaxf(k, o) : k + o;
}

__global__ void __cluster_dims__(2, 1, 1) __launch_bounds__(NTHREADS, 1)
fused_kernel(const __nv_bfloat16* __restrict__ xin, __nv_bfloat16* __restrict__ out, const __nv_bfloat16* __restrict__ wq,
             Scratch* __restrict__ Gp, const __grid_constant__ Maps M) {
  extern __shared__ __align__(1024) uint8_t smem_raw[];
  const uint32_t sm = smem_u32(smem_raw);
  const int tid = threadIdx.x, cta = blockIdx.x;
  const int h = cta >> 2, j = cta & 3, pair = cta >> 1, rank = cta & 1;
  Scratch& G = *Gp;
  const int lane = tid & 31;
  auto bar = [&](int i) { return sm + SM_BAR + 8u * i; };
  const uint32_t epoch = ldg_poll32(&G.epoch[cta]);
  uint4 xu[2][2];
  uint2 xw[2];
  if (tid < 32) {
#pragma unroll
    for (int b = 0; b < 2; b++) {
      const __nv_bfloat16* xp = xin + b * 512 + lane * 16;
      asm volatile("ld.global.nc.v4.u32 {%0,%1,%2,%3}, [%4];" : "=r"(xu[b][0].x), "=r"(xu[b][0].y), "=r"(xu[b][0].z), "=r"(xu[b][0].w) : "l"(xp));
      asm volatile("ld.global.nc.v4.u32 {%0,%1,%2,%3}, [%4];" : "=r"(xu[b][1].x), "=r"(xu[b][1].y), "=r"(xu[b][1].z), "=r"(xu[b][1].w) : "l"(xp + 8));
      asm volatile("ld.global.nc.v2.u32 {%0,%1}, [%2];" : "=r"(xw[b].x), "=r"(xw[b].y) : "l"(xin + b * 512 + 128 * j + 4 * lane));
    }
  }
  if (tid < 256) {
    const int r0 = tid >> 4;
    const char* src = reinterpret_cast<const char*>(wq) + (size_t)(128 * j + r0) * 8192 + h * 256 + (tid & 15) * 16;
    const uint32_t dst = sm + SM_WQ + ((tid >> 3) & 1) * 8192 + r0 * 128 + (((tid & 7) ^ (r0 & 7)) << 4);
    asm volatile(
        "cp.async.cg.shared.global [%0], [%1], 16;\n"
        "cp.async.cg.shared.global [%0 + 2048], [%1 + 131072], 16;\n"
        "cp.async.cg.shared.global [%0 + 4096], [%1 + 262144], 16;\n"
        "cp.async.cg.shared.global [%0 + 6144], [%1 + 393216], 16;\n"
        "cp.async.cg.shared.global [%0 + 16384], [%1 + 524288], 16;\n"
        "cp.async.cg.shared.global [%0 + 18432], [%1 + 655360], 16;\n"
        "cp.async.cg.shared.global [%0 + 20480], [%1 + 786432], 16;\n"
        "cp.async.cg.shared.global [%0 + 22528], [%1 + 917504], 16;"
        ::"r"(dst), "l"(src) : "memory");
  }
  const uint32_t t_start = gtime();

  if (tid >= 256) {
    if (tid < 288) {
      if (lane == 0) {
#pragma unroll
        for (int i = 0; i < NBAR; i++) mbar_init(bar(i), i == BAR_R1FREE ? 8 : 1);
        asm volatile("fence.mbarrier_init.release.cluster;" ::: "memory");
        mbar_expect_tx(bar(BAR_S), 8192);
        mbar_expect_tx(bar(BAR_S + 1), 8192);
#pragma unroll
        for (int i = 0; i < 7; i++) prefetch_map(&M.m[i]);
      }
      __syncwarp();
      bar_arrive(2, NTHREADS);
      asm volatile("barrier.cluster.arrive.relaxed.aligned;" ::: "memory");
      TL(21);
      const int p = lane;
      int mi = 0, c1 = 128 * j + 32 * (p & 3), c2 = 2 * h, c3 = 0, unit = 2 * (p + 1);
      uint32_t dst = SM_WUK + p * 8192u, bytes = 8192;
      if (p >= 4) { mi = 1; c1 = 0; c2 = 4 * rank + (((p - 4) >> 1) & 1) * 2; c3 = 16 * pair + ((p - 4) >> 2) * 8 + (p & 1) * 4; dst = SM_CKV + (p - 4) * 8192u; }
      if (p >= 12) { mi = p - 9; c1 = 128 * j; c2 = 3 * h; c3 = 0; dst = SM_G + (p - 12) * 12288u; bytes = 12288; unit = 3 * p - 9; }
      if (p >= 14) { mi = 2; c1 = 128 * j + 32 * (p - 14); c2 = 2 * h; dst = SM_WUV + (p - 14) * 8192u; bytes = 8192; unit = 2 * p + 4; }
      if (p == 18) { mi = 5; c1 = 48 * h; c2 = 2 * j; dst = SM_WD; bytes = 12288; unit = 41; }
      if (p >= 19) { mi = 6; c1 = 128 * h + 32 * (p - 19); c2 = 2 * j; dst = SM_WO + (p - 19) * 8192u; bytes = 8192; unit = 2 * p + 5; }
      if (STAGGER && p >= 4 && p < 12) unit = (pair & 1) ? 13 + p : 5 + p;
      const uint32_t t_issue = t_start + PACE_T0 + min(unit, 24) * PACE_DT1 + max(unit - 24, 0) * PACE_DT2 + (p >= PAUSE_AT ? PAUSE_NS : 0) + (p >= PAUSE2_AT ? PAUSE2_NS : 0);
      const char* map = reinterpret_cast<const char*>(&M.m[0]) + 128 * mi;
      const uint32_t mybar = bar(p);
      dst += sm;
#pragma unroll 1
      for (int q = 0; q < NPIECE; q++) {
        if (q >= WINDOW) mbar_wait(bar(q - WINDOW));
        if (q == BAR_G) mbar_wait(bar(BAR_R1FREE));
        const uint32_t tq = __shfl_sync(0xffffffffu, t_issue, q);
        int guard = 1 << 16;
        while ((int)(gtime() - tq) < 0 && --guard > 0) {}
        if (lane == q) { mbar_expect_tx(mybar, bytes); tma4d(dst, map, c1, c2, c3, mybar); }
      }
      TL_DUMP(56, 78);
      return;
    }
    asm volatile("barrier.cluster.arrive.relaxed.aligned;" ::: "memory");
    const int oq = ((lane >> 4) & 1) * 4 + ((lane >> 3) & 1) * 2 + ((lane >> 2) & 1);
    const int oidx = (oq & 1) * 512 + 128 * j + 4 * h + (oq >> 1);
    const float xres = __bfloat162float(xin[oidx]);
    const uint32_t par = (epoch + 1u) & 1u, npar = par ^ 1u;
    {
      const uint4 inv = make_uint4(npar, npar, npar, npar);
      uint4* q = reinterpret_cast<uint4*>(&G.x0[cta][0]) + lane;
      stg_pub128(q, inv);
      stg_pub128(q + 32, inv);
      stg_pub128(reinterpret_cast<uint4*>(&G.qlat[lane >> 4][j >> 1][h][(j & 1) * 64]) + (lane & 15), inv);
      bar_arrive(2, NTHREADS);
      TL(23);
      q = reinterpret_cast<uint4*>(&G.x2[cta][0]) + lane;
      stg_pub128(q, inv);
      stg_pub128(q + 32, inv);
      q = reinterpret_cast<uint4*>(&G.x3[j][h][0]) + lane;
      stg_pub128(q, inv);
      stg_pub128(q + 32, inv);
      q = reinterpret_cast<uint4*>(&G.xd[cta][0]) + lane;
      stg_pub128(q, inv);
      if (lane < 16) stg_pub128(q + 32, inv);
      if (rank == 0) { stg_pub32(&G.mx[lane][pair], npar); stg_pub32(&G.ls[lane][pair], npar); }
      bar_arrive(3, 288);
      q = reinterpret_cast<uint4*>(&G.part[pair][rank][0][0][0]) + lane;
#pragma unroll 1
      for (int i = 0; i < 32; i++) {
        int guard = 1 << 16;
        while ((int)(gtime() - (t_start + PRE_T0 + i * PRE_DT)) < 0 && --guard > 0) {}
        stg_pub128(q + 32 * ((i & 7) + ((i >> 3) & 1) * 16 + (i >> 4) * 8), inv);
        if (i == 15) { asm volatile("fence.proxy.async.global;" ::: "memory"); bar_arrive(10, 288); }
      }
      asm volatile("fence.proxy.async.global;" ::: "memory");
      bar_arrive(11, 160);
      bar_arrive(12, 160);
      TL(24);
    }
    {
      uint32_t m0, m1;
      bar_sync(6, 288);
      if (rank == 0) {
        const uint32_t ws = sm + SM_WSUM + lane * 4;
        const float l = (lds32f(ws) + lds32f(ws + 128) + (lds32f(ws + 256) + lds32f(ws + 384))) * ex2(lds32f(sm + SM_M0 + lane * 4) - lds32f(sm + SM_M + lane * 4)) +
                        (lds32f(ws + 512) + lds32f(ws + 640) + (lds32f(ws + 768) + lds32f(ws + 896)));
        stg_pub32(&G.ls[lane][pair], tagf(l, par));
      }
      poll_pair(m0, m1, &G.mx[h][lane], npar);
      float x0 = asf(m0), x1 = asf(m1);
#pragma unroll
      for (int o = 16; o > 0; o >>= 1) { x0 = fmaxf(x0, shx(x0, o)); x1 = fmaxf(x1, shx(x1, o)); }
      const uint32_t wb = pack_bf16(ex2(asf(m0) - x0), ex2(asf(m1) - x1));
      sts16(sm + ACT_W + lane * 2, wb);
      sts16(sm + ACT_W + 64 + lane * 2, 0);
      sts16(sm + ACT_W + ACT_STRIDE + lane * 2, 0);
      sts16(sm + ACT_W + ACT_STRIDE + 64 + lane * 2, wb >> 16);
      bar_arrive(7, 288);
      TL(38);
      spin_clk(M_DELAY);
      poll_pair(m0, m1, &G.ls[h][lane], npar);
      x0 = bf_lo(wb) * asf(m0);
      x1 = bf_hi(wb) * asf(m1);
#pragma unroll
      for (int o = 16; o > 0; o >>= 1) { x0 += shx(x0, o); x1 += shx(x1, o); }
      if (lane == 0) { sts32f(sm + SM_INVL, 1.f / x0); sts32f(sm + SM_INVL + 4, 1.f / x1); }
      TL(39);
      uint4 v[4], u[2][4];
      const char* src = reinterpret_cast<const char*>(&G.xd[4 * h][4 * lane]);
      const char* src2 = reinterpret_cast<const char*>(&G.xd[4 * h][128 + 4 * (lane & 15)]);
      int it = kPollLimit;
      bool ok;
      do {
        poll_issue<4>(u[0], src, 768);
        poll_issue<4>(u[1], src2, 768);
        ok = true;
#pragma unroll
        for (int q = 0; q < 4; q++) ok = ok && ok4(u[0][q], npar) && ok4(u[1][q], npar);
      } while (!__all_sync(0xffffffffu, ok) && --it > 0);
      (void)v;
#pragma unroll
      for (int e = 0; e < 2; e++) {
        const uint4 (&w)[4] = u[e];
        const float s0 = asf(w[0].x) + asf(w[1].x) + (asf(w[2].x) + asf(w[3].x)), s1 = asf(w[0].y) + asf(w[1].y) + (asf(w[2].y) + asf(w[3].y));
        const float s2 = asf(w[0].z) + asf(w[1].z) + (asf(w[2].z) + asf(w[3].z)), s3 = asf(w[0].w) + asf(w[1].w) + (asf(w[2].w) + asf(w[3].w));
        const uint32_t hh = pack_bf16(__fdividef(s2, 1.f + __expf(-s0)), __fdividef(s3, 1.f + __expf(-s1)));
        if (e == 0 || lane < 16) {
          sts16(sm + ACT_H + 2 * (32 * e + lane), hh);
          sts16(sm + ACT_H + ACT_STRIDE + 2 * (32 * e + lane), hh >> 16);
        }
      }
      bar_arrive(8, 288);
      TL(27);
    }
    {
      const float* src = &G.x3[j][lane][8 * h];
      uint4 xv[2];
      bar_sync(9, 288);
      spin_clk(X3_DELAY);
      TL(28);
      poll_issue<2>(xv, reinterpret_cast<const char*>(src), 16);
      poll_finish<2, GAP2>(xv, reinterpret_cast<const char*>(src), 16, npar);
      __syncwarp();
      const uint4 a = xv[0], b = xv[1];
      TL(34);
      float v[8] = {asf(a.x), asf(a.y), asf(a.z), asf(a.w), asf(b.x), asf(b.y), asf(b.z), asf(b.w)};
      float r = col_reduce<false>(v, lane);
      r += shx(r, 2);
      r += shx(r, 1);
      if ((lane & 3) == 0) out[oidx] = __float2bfloat16(xres + r);
      if (lane == 0) G.epoch[cta] = epoch + 1;
      TL(35);
      TL_DUMP(34, 36);
      TL_DUMP(38, 40);
      TL_DUMP(27, 32);
    }
    return;
  }

  const int warp = tid >> 5;
  const int g = lane >> 2, t = lane & 3;
  if (warp == 0) {
      const uint4 (&u)[2][2] = xu;
      float s[2], ss[2];
#pragma unroll
      for (int b = 0; b < 2; b++) {
        const uint32_t w[8] = {u[b][0].x, u[b][0].y, u[b][0].z, u[b][0].w, u[b][1].x, u[b][1].y, u[b][1].z, u[b][1].w};
        s[b] = 0.f;
#pragma unroll
        for (int q = 0; q < 8; q++) s[b] += bf_lo(w[q]) + bf_hi(w[q]);
      }
#pragma unroll
      for (int o = 16; o > 0; o >>= 1) { s[0] += shx(s[0], o); s[1] += shx(s[1], o); }
#pragma unroll
      for (int b = 0; b < 2; b++) {
        const uint32_t w[8] = {u[b][0].x, u[b][0].y, u[b][0].z, u[b][0].w, u[b][1].x, u[b][1].y, u[b][1].z, u[b][1].w};
        s[b] *= 1.f / 512.f;
        ss[b] = 0.f;
#pragma unroll
        for (int q = 0; q < 8; q++) { const float d0 = bf_lo(w[q]) - s[b], d1 = bf_hi(w[q]) - s[b]; ss[b] += d0 * d0 + d1 * d1; }
      }
#pragma unroll
      for (int o = 16; o > 0; o >>= 1) { ss[0] += shx(ss[0], o); ss[1] += shx(ss[1], o); }
#pragma unroll
      for (int b = 0; b < 2; b++) {
        const float r = rsqrtf(ss[b] * (1.f / 512.f) + 1e-5f);
        act_store_hilo(sm + ACT_X + b * ACT_STRIDE + 8 * lane, (bf_lo(xw[b].x) - s[b]) * r, (bf_hi(xw[b].x) - s[b]) * r);
        act_store_hilo(sm + ACT_X + b * ACT_STRIDE + 8 * lane + 4, (bf_lo(xw[b].y) - s[b]) * r, (bf_hi(xw[b].y) - s[b]) * r);
      }
    }
  TL(22);
  const uint32_t par = (epoch + 1u) & 1u, npar = par ^ 1u;
  asm volatile("cp.async.wait_all;" ::: "memory");
  TL(1);
  bar_sync(2, NTHREADS);
  TLB(2);

  const int mat = lane >> 3, l7 = lane & 7;
  const int tr_row = l7 + (mat >> 1) * 8;
  const uint32_t tr_off = sm + tr_row * 128 + ((((warp & 3) * 2 + (mat & 1)) ^ l7) << 4);
  const uint32_t tr_cb = warp >> 2;
  const uint32_t bf4 = sm + (l7 & 3) * ACT_STRIDE + mat * 16;
  const uint32_t bf2 = sm + (l7 & 1) * ACT_STRIDE + mat * 16;

  {
    float d[4], e[4];
    uint32_t b[4][4], a[8][4];
#pragma unroll
    for (int q = 0; q < 4; q++) ldsm4(b[q], bf4 + ACT_X + 64 * q);
#pragma unroll
    for (int s = 0; s < 8; s++) ldsm4t(a[s], tr_off + SM_WQ + (s >> 2) * 16384 + tr_cb * 8192 + (s & 3) * 2048);
    mma16816z(d, a[0], b[0][0], b[0][1]);
    mma16816z(e, a[1], b[0][2], b[0][3]);
#pragma unroll
    for (int q = 1; q < 4; q++) { mma16816(d, a[2 * q], b[q][0], b[q][1]); mma16816(e, a[2 * q + 1], b[q][2], b[q][3]); }
    float r0 = d[0] + e[0], r1 = d[1] + e[1], r2 = d[2] + e[2], r3 = d[3] + e[3];
    const float k0 = (t & 1) ? r2 : r0, k1 = (t & 1) ? r3 : r1, s0 = (t & 1) ? r0 : r2, s1 = (t & 1) ? r1 : r3;
    r0 = k0 + shx(s0, 1); r1 = k1 + shx(s1, 1);
    if (t < 2) stg_pub64(&G.x0[cta][(16 * warp + g + 8 * t) * 2], tagf(r0, par), tagf(r1, par));
  }
  TL(3);
  if (tid < 64) {
    uint4 v[4];
    mbar_wait(bar(BAR_WUK + X0_PIECE));
    TL(40);
    poll_issue<4>(v, reinterpret_cast<const char*>(&G.x0[4 * h][4 * tid]), 1024);
    poll_finish<4, GAP2>(v, reinterpret_cast<const char*>(&G.x0[4 * h][4 * tid]), 1024, npar POLL_TL(40));
    const float sc = 0.08838834764831845f * 1.4426950408889634f;
    act_store_hilo(sm + ACT_Q + 4 * tid, (asf(v[0].x) + asf(v[1].x) + asf(v[2].x) + asf(v[3].x)) * sc, (asf(v[0].z) + asf(v[1].z) + asf(v[2].z) + asf(v[3].z)) * sc);
    act_store_hilo(sm + ACT_Q + ACT_STRIDE + 4 * tid, (asf(v[0].y) + asf(v[1].y) + asf(v[2].y) + asf(v[3].y)) * sc, (asf(v[0].w) + asf(v[1].w) + asf(v[2].w) + asf(v[3].w)) * sc);
  }
  bar_compute();
  TLB(4);
  {
    float d[4], e[4];
    const int row = (warp & 1) * 16 + l7 + (mat & 1) * 8;
    uint32_t b[4][4];
#pragma unroll
    for (int q = 0; q < 4; q++) ldsm4(b[q], bf4 + ACT_Q + 64 * q);
    mbar_wait(bar(BAR_WUK + (warp >> 1)));
    const uint32_t abase = sm + SM_WUK + (warp >> 1) * 8192 + row * 128;
#pragma unroll
    for (int q = 0; q < 4; q++) {
      uint32_t a0[4], a1[4];
      ldsm4(a0, abase + (q >> 1) * 4096 + ((((q & 1) * 4 + (mat >> 1)) ^ l7) << 4));
      ldsm4(a1, abase + (q >> 1) * 4096 + ((((q & 1) * 4 + 2 + (mat >> 1)) ^ l7) << 4));
      if (q == 0) { mma16816z(d, a0, b[0][0], b[0][1]); mma16816z(e, a1, b[0][2], b[0][3]); }
      else { mma16816(d, a0, b[q][0], b[q][1]); mma16816(e, a1, b[q][2], b[q][3]); }
    }
    float r0 = d[0] + e[0], r1 = d[1] + e[1], r2 = d[2] + e[2], r3 = d[3] + e[3];
    const float k0 = (t & 1) ? r2 : r0, k1 = (t & 1) ? r3 : r1, s0 = (t & 1) ? r0 : r2, s1 = (t & 1) ? r1 : r3;
    r0 = k0 + shx(s0, 1); r1 = k1 + shx(s1, 1);
    sts32f(sm + SM_QST + (t >> 1) * 512 + (16 * warp + g + 8 * (t & 1)) * 4, (t & 2) ? r1 : r0);
    __syncwarp();
    if (lane == 0) mbar_arrive(bar(BAR_R1FREE));
    asm volatile("barrier.cluster.arrive.relaxed.aligned;" ::: "memory");
    bar_compute();
    if (tid < 128) {
      const float2 v = lds64f(sm + SM_QST + tid * 8);
      stg_pub32(&G.qlat[tid >> 6][j >> 1][h][(j & 1) * 64 + (tid & 63)], (pack_bf16(v.x, v.y) & ~1u) | par);
    }
  }
  TL(5);
  {
    mbar_wait(bar(BAR_CKV + XQ_PIECE));
    uint4 v[4];
    TL(44);
    poll_issue<4>(v, reinterpret_cast<const char*>(&G.qlat[pair >> 5][rank][0][0]) + tid * 16, 4096);
    poll_finish<4, GAP1>(v, reinterpret_cast<const char*>(&G.qlat[pair >> 5][rank][0][0]) + tid * 16, 4096, npar POLL_TL(44));
    const int hh = tid >> 5, pc = tid & 31;
    const uint32_t dst = sm + SM_QB + (pc >> 3) * 4096 + hh * 128 + (((pc & 7) ^ (hh & 7)) << 4);
#pragma unroll
    for (int i = 0; i < 4; i++) sts128(dst + i * 1024, make_uint4(v[i].x & ~1u, v[i].y & ~1u, v[i].z & ~1u, v[i].w & ~1u));
    fence_async_smem();
    asm volatile("barrier.cluster.wait.aligned;" ::: "memory");
    bar_sync(3, 288);
  }
  TLB(6);
  const int wg = warp >> 2, wq4 = warp & 3;
  const int mycol = ((lane >> 3) & 3) * 8 + (lane & 3) * 2 + ((lane >> 2) & 1);
  float s[16], o0[16], o1[16];
  uint32_t pa[16][4];
  def_regs(s);
  def_regs(o0);
  def_regs(o1);
  const uint64_t dbp = make_desc(sm + SM_P, 1024);
  const uint32_t pbase = sm + SM_CKV + wg * 16384 + (mat >> 1) * 2048 + l7 * 128 + (((wq4 * 2 + (mat & 1)) ^ l7) << 4);
  auto pv_first = [&]() {
    wgmma_fence();
#pragma unroll
    for (int k = 0; k < 4; k++) {
      if (k == 0) wgmma_rs<false>(o0, pa[0], dbp);
      else wgmma_rs<true>(o0, pa[k], dbp + ((k * 32) >> 4));
    }
#pragma unroll
    for (int k = 0; k < 4; k++) {
      if (k == 0) wgmma_rs<false>(o1, pa[8], dbp);
      else wgmma_rs<true>(o1, pa[8 + k], dbp + ((k * 32) >> 4));
    }
    wgmma_commit();
  };
  auto load_second = [&]() {
    mbar_wait(bar(BAR_CKV + 4 + wg * 2));
    mbar_wait(bar(BAR_CKV + 4 + wg * 2 + 1));
#pragma unroll
    for (int q = 0; q < 8; q++) ldsm4t(pa[(q >> 2) * 8 + 4 + (q & 3)], pbase + 32768 + (q >> 2) * 1024 + (q & 3) * 4096);
  };
  auto row_sums = [&]() {
    float v[8];
#pragma unroll
    for (int i = 0; i < 4; i++) { v[2 * i] = s[4 * i] + s[4 * i + 2]; v[2 * i + 1] = s[4 * i + 1] + s[4 * i + 3]; }
    sts32f(sm + SM_WSUM + warp * 128 + mycol * 4, col_reduce<false>(v, lane));
    bar_arrive(6, 288);
  };
  {
    const uint64_t da = make_desc(sm + SM_CKV + wg * 32768, 2048), db = make_desc(sm + SM_QB, 1024);
#pragma unroll
    for (int cp = 0; cp < 2; cp++) {
      mbar_wait(bar(BAR_CKV + wg * 4 + cp * 2));
      mbar_wait(bar(BAR_CKV + wg * 4 + cp * 2 + 1));
      wgmma_fence();
#pragma unroll
      for (int k = 0; k < 8; k++) {
        const int blk = k >> 2, ks = k & 3;
        if (cp == 0 && k == 0) wgmma_ss<false>(s, da, db);
        else wgmma_ss<true>(s, da + ((cp * 16384 + blk * 1024 + ks * 32) >> 4), db + (((cp * 2 + blk) * 4096 + ks * 32) >> 4));
      }
      wgmma_commit();
      if (cp == 0) {
        mbar_wait(bar(BAR_CKV + wg * 2));
        mbar_wait(bar(BAR_CKV + wg * 2 + 1));
#pragma unroll
        for (int q = 0; q < 8; q++) ldsm4t(pa[(q >> 2) * 8 + (q & 3)], pbase + (q >> 2) * 1024 + (q & 3) * 4096);
      }
    }
    uint32_t rdst, rbar;
    asm volatile("mapa.shared::cluster.u32 %0, %1, %2;" : "=r"(rdst) : "r"(sm + SM_SRECV + tid * 16), "r"(rank ^ 1));
    asm volatile("mapa.shared::cluster.u32 %0, %1, %2;" : "=r"(rbar) : "r"(bar(BAR_S + wg)), "r"(rank ^ 1));
    wgmma_wait<0>();
    fence_regs(s);
    TL(7); TLW(17);
#pragma unroll
    for (int q = 0; q < 4; q++)
      asm volatile("st.async.weak.shared::cluster.mbarrier::complete_tx::bytes.v4.f32 [%0], {%1,%2,%3,%4}, [%5];"
                   ::"r"(rdst + q * 4096), "f"(s[4 * q]), "f"(s[4 * q + 1]), "f"(s[4 * q + 2]), "f"(s[4 * q + 3]), "r"(rbar) : "memory");
    if (wg == 1) load_second();
    mbar_wait(bar(BAR_S + wg));
#pragma unroll
    for (int q = 0; q < 4; q++) {
      const uint4 o = lds128(sm + SM_SRECV + tid * 16 + q * 4096);
      s[4 * q] += asf(o.x); s[4 * q + 1] += asf(o.y); s[4 * q + 2] += asf(o.z); s[4 * q + 3] += asf(o.w);
    }
  }
  TL(8); TLW(18);
  {
    float v[8];
#pragma unroll
    for (int i = 0; i < 4; i++) { v[2 * i] = fmaxf(s[4 * i], s[4 * i + 2]); v[2 * i + 1] = fmaxf(s[4 * i + 1], s[4 * i + 3]); }
    sts32f(sm + SM_WMAX + warp * 128 + mycol * 4, col_reduce<true>(v, lane));
    bar_sync(4 + wg, 128);
    TLW(19);
    const uint32_t wm = sm + SM_WMAX + wg * 512 + mycol * 4;
    float m = fmaxf(fmaxf(lds32f(wm), lds32f(wm + 128)), fmaxf(lds32f(wm + 256), lds32f(wm + 384)));
    float m0 = m;
    if (wg == 0) {
      if (warp == 0) sts32f(sm + SM_M0 + mycol * 4, m);
    } else {
      bar_sync(13, 256);
      m0 = lds32f(sm + SM_M0 + mycol * 4);
      m = asf(tagf(fmaxf(m, m0), par));
      if (warp == 4) {
        sts32f(sm + SM_M + mycol * 4, m);
        if (rank == 0) stg_pub32(&G.mx[mycol][pair], __float_as_uint(m));
      }
      bar_arrive(14, 256);
      pv_first();
    }
#pragma unroll
    for (int i = 0; i < 4; i++) {
      const float ma = __shfl_sync(0xffffffffu, m, (i << 3) | t), mb = __shfl_sync(0xffffffffu, m, (i << 3) | 4 | t);
      s[4 * i] = ex2(s[4 * i] - ma); s[4 * i + 1] = ex2(s[4 * i + 1] - mb);
      s[4 * i + 2] = ex2(s[4 * i + 2] - ma); s[4 * i + 3] = ex2(s[4 * i + 3] - mb);
    }
#pragma unroll
    for (int c2 = 0; c2 < 2; c2++) {
      const int i = 2 * c2 + (mat >> 1), hh = 8 * i + l7, kc = wq4 * 2 + (mat & 1);
      stsm4t(sm + SM_P + wg * 4096 + hh * 128 + ((kc ^ l7) << 4),
             pack_bf16(s[8 * c2], s[8 * c2 + 1]), pack_bf16(s[8 * c2 + 2], s[8 * c2 + 3]),
             pack_bf16(s[8 * c2 + 4], s[8 * c2 + 5]), pack_bf16(s[8 * c2 + 6], s[8 * c2 + 7]));
    }
    fence_async_smem();
    if (wg == 0) {
      bar_sync(4, 128);
      bar_arrive(13, 256);
      pv_first();
      row_sums();
      load_second();
      bar_sync(14, 256);
      m = lds32f(sm + SM_M + mycol * 4);
    }
    const float f = ex2(m0 - m);
    wgmma_wait<0>();
    fence_regs(o0);
    fence_regs(o1);
#pragma unroll
    for (int i = 0; i < 4; i++) {
      const float fa = __shfl_sync(0xffffffffu, f, (i << 3) | t), fb = __shfl_sync(0xffffffffu, f, (i << 3) | 4 | t);
      o0[4 * i] *= fa; o0[4 * i + 1] *= fb; o0[4 * i + 2] *= fa; o0[4 * i + 3] *= fb;
      o1[4 * i] *= fa; o1[4 * i + 1] *= fb; o1[4 * i + 2] *= fa; o1[4 * i + 3] *= fb;
    }
    bar_sync(10, 288);
  }
  TLB(9);
  {
    fence_regs(o0);
    fence_regs(o1);
    wgmma_fence();
#pragma unroll
    for (int k = 4; k < 8; k++) wgmma_rs<true>(o0, pa[k], dbp + ((4096 + (k & 3) * 32) >> 4));
    wgmma_commit();
#pragma unroll
    for (int k = 4; k < 8; k++) wgmma_rs<true>(o1, pa[8 + k], dbp + ((4096 + (k & 3) * 32) >> 4));
    wgmma_commit();
    if (wg == 1) row_sums();
    const uint32_t am = (g & 1) ? 0xffffffffu : 0xfffefffeu, om = (g & 1) ? 0u : par * 0x10001u;
    const uint32_t st0 = sm + SM_QB + wg * 8192 + (8 * (mat >> 1) + l7) * 128 + (((wq4 * 2 + (mat & 1)) ^ l7) << 4);
    auto publish = [&](float (&o)[16], int half) {
      fence_regs(o);
#pragma unroll
      for (int c2 = 0; c2 < 2; c2++)
        stsm4t(st0 + half * 4096 + c2 * 2048, (pack_bf16(o[8 * c2], o[8 * c2 + 1]) & am) | om, (pack_bf16(o[8 * c2 + 2], o[8 * c2 + 3]) & am) | om,
               (pack_bf16(o[8 * c2 + 4], o[8 * c2 + 5]) & am) | om, (pack_bf16(o[8 * c2 + 6], o[8 * c2 + 7]) & am) | om);
      fence_async_smem();
      if (half == 0) bar_sync(4 + wg, 128); else bar_sync(11 + wg, 160);
      if ((tid & 127) == 0) {
        asm volatile("cp.async.bulk.global.shared::cta.bulk_group [%0], [%1], %2;"
                     ::"l"(&G.part[pair][rank][wg * 2 + half][0][0]), "r"(sm + SM_QB + wg * 8192 + half * 4096), "r"(4096) : "memory");
        asm volatile("cp.async.bulk.commit_group;" ::: "memory");
      }
    };
    wgmma_wait<1>();
    TL(20);
    publish(o0, 0);
    wgmma_wait<0>();
    TL(10);
    publish(o1, 1);
  }
  TL(11);
  if (warp < 6) {
    const int m2 = warp >= 3, tile = warp - 3 * m2;
    float d[4], e[4];
    uint32_t b[4][4];
#pragma unroll
    for (int q = 0; q < 4; q++) ldsm4(b[q], bf4 + ACT_X + 64 * q);
    mbar_wait(bar(BAR_G + m2));
    const uint32_t abase = sm + SM_G + m2 * 12288 + tile * 4096 + tr_row * 32 + (((mat & 1) ^ ((tr_row >> 2) & 1)) << 4);
#pragma unroll
    for (int q = 0; q < 4; q++) {
      uint32_t a0[4], a1[4];
      ldsm4t(a0, abase + q * 1024);
      ldsm4t(a1, abase + q * 1024 + 512);
      if (q == 0) { mma16816z(d, a0, b[0][0], b[0][1]); mma16816z(e, a1, b[0][2], b[0][3]); }
      else { mma16816(d, a0, b[q][0], b[q][1]); mma16816(e, a1, b[q][2], b[q][3]); }
    }
    float r0 = d[0] + e[0], r1 = d[1] + e[1], r2 = d[2] + e[2], r3 = d[3] + e[3];
    const float k0 = (t & 1) ? r2 : r0, k1 = (t & 1) ? r3 : r1, s0 = (t & 1) ? r0 : r2, s1 = (t & 1) ? r1 : r3;
    r0 = k0 + shx(s0, 1); r1 = k1 + shx(s1, 1);
    if (t < 2) stg_pub64(&G.xd[cta][(16 * tile + g + 8 * t) * 4 + 2 * m2], tagf(r0, par), tagf(r1, par));
  }
  TL(15);
  uint32_t wf[8][4];
  {
    const int rg = (tid & 127) >> 3, pc = (tid & 7) + 8 * wg;
    uint4 v[4];
    const char* src = reinterpret_cast<const char*>(&G.part[rg][j >> 1][(j & 1) * 2 + wg][h][0]) + (((pc & 7) ^ (h & 7)) << 4);
    spin_clk(wg == 0 ? X1_DELAY : X1_DELAY_B);
    TL(48);
    poll_issue<4>(v, src, 16 * 32768);
#pragma unroll
    for (int q = 0; q < 4; q++) mbar_wait(bar(BAR_WUV + q));
#pragma unroll
    for (int q = 0; q < 8; q++) ldsm4t(wf[q], tr_off + SM_WUV + (q >> 1) * 8192 + tr_cb * 4096 + (q & 1) * 2048);
    poll_finish<4, GAP1>(v, src, 16 * 32768, npar POLL_TL(48));
    TL(12);
    const uint32_t dst = sm + SM_CKV + (pc >> 3) * 8192 + rg * 128 + (((pc & 7) ^ (rg & 7)) << 4);
#pragma unroll
    for (int i = 0; i < 4; i++) sts128(dst + i * 2048, make_uint4(v[i].x & ~1u, v[i].y & ~1u, v[i].z & ~1u, v[i].w & ~1u));
    bar_sync(7, 288);
    TLB(32);
    float d[4], e[4];
    uint32_t b[2][4], a[4][4];
    ldsm4(b[0], bf2 + ACT_W);
    ldsm4(b[1], bf2 + ACT_W + 64);
#pragma unroll
    for (int s4 = 0; s4 < 4; s4++) ldsm4t(a[s4], tr_off + SM_CKV + tr_cb * 8192 + s4 * 2048);
    mma16816z(d, a[0], b[0][0], b[0][1]);
    mma16816z(e, a[1], b[0][2], b[0][3]);
    mma16816(d, a[2], b[1][0], b[1][1]);
    mma16816(e, a[3], b[1][2], b[1][3]);
    const float val = (t & 2) ? ((t & 1) ? d[3] + e[3] : d[2] + e[2]) : ((t & 1) ? d[1] + e[1] : d[0] + e[0]);
    sts16(sm + ACT_CL + (t & 1) * ACT_STRIDE + (16 * warp + g + 8 * (t >> 1)) * 2, pack_bf16(val, 0.f));
    bar_compute();
  }
  TLB(13);
  {
    float d[4][4];
    uint32_t b[4][4];
#pragma unroll
    for (int q = 0; q < 4; q++) ldsm4(b[q], bf2 + ACT_CL + 64 * q);
#pragma unroll
    for (int q = 0; q < 4; q++) mma16816z(d[q], wf[2 * q], b[q][0], b[q][1]);
#pragma unroll
    for (int q = 0; q < 4; q++) mma16816(d[q], wf[2 * q + 1], b[q][2], b[q][3]);
    const int o = (t & 1) * 2;
    const float r0 = o ? d[0][2] + d[1][2] + (d[2][2] + d[3][2]) : d[0][0] + d[1][0] + (d[2][0] + d[3][0]);
    const float r1 = o ? d[0][3] + d[1][3] + (d[2][3] + d[3][3]) : d[0][1] + d[1][1] + (d[2][1] + d[3][1]);
    if (t < 2) stg_pub64(&G.x2[cta][(16 * warp + g + 8 * t) * 2], tagf(r0, par), tagf(r1, par));
  }
  TL(14);
  uint32_t wd[3][4];
  {
    uint4 v[4];
    const char* src = reinterpret_cast<const char*>(&G.x2[4 * h][4 * tid]);
    if (tid < 64) {
      if (X2_DELAY > 0) spin_clk(X2_DELAY);
      TL(52);
      poll_issue<4>(v, src, 1024);
    }
    mbar_wait(bar(BAR_WD));
#pragma unroll
    for (int s3 = 0; s3 < 3; s3++) ldsm4t(wd[s3], tr_off + SM_WD + tr_cb * 6144 + s3 * 2048);
#pragma unroll
    for (int p = 0; p < 3; p++) {
      mbar_wait(bar(BAR_WO + p));
      ldsm4t(wf[2 * p], tr_off + SM_WO + p * 8192 + tr_cb * 4096);
      ldsm4t(wf[2 * p + 1], tr_off + SM_WO + p * 8192 + tr_cb * 4096 + 2048);
    }
    if (tid < 64) {
      poll_finish<4, GAP2>(v, src, 1024, npar POLL_TL(52));
      const float s0 = asf(v[0].x) + asf(v[1].x) + (asf(v[2].x) + asf(v[3].x)), s1 = asf(v[0].y) + asf(v[1].y) + (asf(v[2].y) + asf(v[3].y));
      const float s2 = asf(v[0].z) + asf(v[1].z) + (asf(v[2].z) + asf(v[3].z)), s3 = asf(v[0].w) + asf(v[1].w) + (asf(v[2].w) + asf(v[3].w));
      sts32(sm + ACT_CTX + 4 * tid, pack_bf16(s0, s2));
      sts32(sm + ACT_CTX + ACT_STRIDE + 4 * tid, pack_bf16(s1, s3));
    }
    mbar_wait(bar(BAR_WO + 3));
    ldsm4t(wf[6], tr_off + SM_WO + 3 * 8192 + tr_cb * 4096);
    ldsm4t(wf[7], tr_off + SM_WO + 3 * 8192 + tr_cb * 4096 + 2048);
  }
  bar_sync(8, 288);
  TLB(36);
  {
    float d[4], e[4], f[4];
    uint32_t b[4][4], bh[2][4];
#pragma unroll
    for (int q = 0; q < 4; q++) ldsm4(b[q], bf2 + ACT_CTX + 64 * q);
    ldsm4(bh[0], bf2 + ACT_H);
    ldsm4(bh[1], bf2 + ACT_H + 64);
    const float2 il = lds64f(sm + SM_INVL);
    mma16816z(d, wf[0], b[0][0], b[0][1]);
    mma16816z(e, wf[1], b[0][2], b[0][3]);
    mma16816z(f, wd[0], bh[0][0], bh[0][1]);
#pragma unroll
    for (int p = 1; p < 4; p++) {
      mma16816(d, wf[2 * p], b[p][0], b[p][1]);
      mma16816(e, wf[2 * p + 1], b[p][2], b[p][3]);
      if (p == 1) mma16816(f, wd[1], bh[0][2], bh[0][3]);
      if (p == 2) mma16816(f, wd[2], bh[1][0], bh[1][1]);
    }
    const float r0 = (t & 1) ? (d[2] + e[2]) * il.x + f[2] : (d[0] + e[0]) * il.x + f[0];
    const float r1 = (t & 1) ? (d[3] + e[3]) * il.y + f[3] : (d[1] + e[1]) * il.y + f[1];
    if (t < 2) stg_pub64(&G.x3[j][h][(16 * warp + g + 8 * t) * 2], tagf(r0, par), tagf(r1, par));
  }
  bar_arrive(9, 288);
  TL(37);
  if ((tid & 127) == 0) asm volatile("cp.async.bulk.wait_group 0;" ::: "memory");
}

typedef CUresult (*EncodeFn)(CUtensorMap*, CUtensorMapDataType, cuuint32_t, void*, const cuuint64_t*, const cuuint64_t*,
                             const cuuint32_t*, const cuuint32_t*, CUtensorMapInterleave, CUtensorMapSwizzle,
                             CUtensorMapL2promotion, CUtensorMapFloatOOBfill);

static void make_map(EncodeFn enc, CUtensorMap* m, const void* base, uint64_t inner, uint64_t d1, uint64_t s1, uint64_t d2,
                     uint64_t s2, uint64_t d3, uint64_t s3, uint32_t b1, uint32_t b2, uint32_t b3, CUtensorMapSwizzle sw) {
  cuuint64_t dims[4] = {inner, d1, d2, d3};
  cuuint64_t strides[3] = {s1, s2, s3};
  cuuint32_t box[4] = {(cuuint32_t)inner, b1, b2, b3};
  cuuint32_t es[4] = {1, 1, 1, 1};
  enc(m, CU_TENSOR_MAP_DATA_TYPE_BFLOAT16, 4, const_cast<void*>(base), dims, strides, box, es, CU_TENSOR_MAP_INTERLEAVE_NONE, sw,
      CU_TENSOR_MAP_L2_PROMOTION_L2_128B, CU_TENSOR_MAP_FLOAT_OOB_FILL_NONE);
}

}

extern "C" void kernel_launch(void* const* d_in, const int* in_sizes, int n_in, void* d_out, int out_size) {
  using namespace mla;
  (void)in_sizes; (void)n_in; (void)out_size;
  static EncodeFn enc = nullptr;
  static Scratch* scr = nullptr;
  if (!enc) {
    void* fn = nullptr;
    cudaDriverEntryPointQueryResult st;
    cudaGetDriverEntryPoint("cuTensorMapEncodeTiled", &fn, cudaEnableDefault, &st);
    enc = (EncodeFn)fn;
    cudaFuncSetAttribute(fused_kernel, cudaFuncAttributeMaxDynamicSharedMemorySize, (int)SM_TOTAL);
    void* p = nullptr;
    cudaGetSymbolAddress(&p, g_scr);
    scr = (Scratch*)p;
  }
  Maps m;
  const uint64_t big = 1ull << 24;
  make_map(enc, &m.m[0], d_in[3], 64, 512, 8192, 64, 128, 1, big, 32, 2, 1, CU_TENSOR_MAP_SWIZZLE_128B);
  make_map(enc, &m.m[1], d_in[1], 64, 8, 1024, 8, 128, 1024, 8192, 8, 2, 4, CU_TENSOR_MAP_SWIZZLE_128B);
  make_map(enc, &m.m[2], d_in[4], 64, 512, 8192, 64, 128, 1, big, 32, 2, 1, CU_TENSOR_MAP_SWIZZLE_128B);
  make_map(enc, &m.m[3], d_in[7], 16, 512, 2752, 86, 32, 1, big, 128, 3, 1, CU_TENSOR_MAP_SWIZZLE_32B);
  make_map(enc, &m.m[4], d_in[8], 16, 512, 2752, 86, 32, 1, big, 128, 3, 1, CU_TENSOR_MAP_SWIZZLE_32B);
  make_map(enc, &m.m[5], d_in[9], 64, 1376, 1024, 8, 128, 1, big, 48, 2, 1, CU_TENSOR_MAP_SWIZZLE_128B);
  make_map(enc, &m.m[6], d_in[5], 64, 4096, 1024, 8, 128, 1, big, 32, 2, 1, CU_TENSOR_MAP_SWIZZLE_128B);
  fused_kernel<<<NCTA, NTHREADS, SM_TOTAL>>>((const __nv_bfloat16*)d_in[0], (__nv_bfloat16*)d_out, (const __nv_bfloat16*)d_in[2], scr, m);
}
```

```cpp
#include <cuda_runtime.h>
#include <cuda_bf16.h>
#include <cuda.h>
#include <stdint.h>

#define DEVI __device__ __forceinline__

namespace mla {

constexpr int NCTA = 128;
constexpr int NTHREADS = 320;
constexpr int kPollLimit = 1 << 18;
#define PACE_T0 1000
#define PACE_DT1 160
#define PACE_DT2 163
#define WINDOW 4
#define PAUSE_AT 18
#define PAUSE_NS 520
#define PRE_T0 2500
#define PRE_DT 80
#define X0_PIECE 1
#define XQ_PIECE 1
#define X1_DELAY 1300
#define X1_DELAY_B 1900
#define X1_T 8200
#define X1_T_B 8550
#define X1_MIN 0
#define X1_MIN_B 200
#define M_DELAY 600
#define PV_PRE 2
#define X2_DELAY 600
#define X2_MIN 250
#define X2_T 9900
#define X3_DELAY 340

constexpr uint32_t SM_WQ = 0;
constexpr uint32_t SM_WUK = 32768;
constexpr uint32_t SM_G = 0;
constexpr uint32_t SM_WD = 24576;
constexpr uint32_t SM_SRECV = 36864;
constexpr uint32_t SM_P = 53248;
constexpr uint32_t SM_CKV = 65536;
constexpr uint32_t SM_WUV = 131072;
constexpr uint32_t SM_WO = 163840;
constexpr uint32_t SM_QB = 196608;
constexpr uint32_t SM_ACT = 212992;
constexpr uint32_t ACT_STRIDE = 272;
constexpr uint32_t ACT_X = SM_ACT, ACT_Q = SM_ACT + 1088;
constexpr uint32_t ACT_CL = SM_ACT + 2176, ACT_CTX = ACT_CL + 544, ACT_H = ACT_CTX + 544, ACT_W = ACT_H + 544;
constexpr uint32_t SM_INVL = ACT_W + 544;
constexpr uint32_t SM_WMAX = SM_INVL + 64;
constexpr uint32_t SM_WSUM = SM_WMAX + 1024;
constexpr uint32_t SM_QST = SM_WSUM + 1024;
constexpr uint32_t SM_BAR = SM_QST + 1024;
constexpr uint32_t SM_TOTAL = SM_BAR + 576;
static_assert(SM_BAR % 8 == 0 && SM_WMAX % 16 == 0, "alignment");

constexpr int NPIECE = 23;
constexpr int BAR_WUK = 0, BAR_CKV = 4, BAR_G = 12, BAR_WUV = 14, BAR_WD = 18, BAR_WO = 19,
              BAR_R1FREE = 23, BAR_S = 24, NBAR = 26;

struct alignas(64) Maps { CUtensorMap m[7]; };

struct Scratch {
  uint32_t part[64][2][4][32][32];
  uint32_t qlat[2][2][32][128];
  float x0[NCTA][256];
  float x2[NCTA][256];
  float x3[4][32][256];
  float xd[NCTA][192];
  float mx[32][64];
  float ls[32][64];
  uint32_t epoch[NCTA];
};
__device__ Scratch g_scr;

DEVI uint32_t smem_u32(const void* p) { return (uint32_t)__cvta_generic_to_shared(p); }
DEVI void mbar_init(uint32_t bar, uint32_t cnt) { asm volatile("mbarrier.init.shared::cta.b64 [%0], %1;" ::"r"(bar), "r"(cnt) : "memory"); }
DEVI void mbar_expect_tx(uint32_t bar, uint32_t bytes) { asm volatile("mbarrier.arrive.expect_tx.shared::cta.b64 _, [%0], %1;" ::"r"(bar), "r"(bytes) : "memory"); }
DEVI void mbar_arrive(uint32_t bar) { asm volatile("mbarrier.arrive.shared::cta.b64 _, [%0];" ::"r"(bar) : "memory"); }
DEVI void mbar_wait(uint32_t bar) {
  asm volatile(
      "{\n.reg .pred p, q;\n.reg .s32 c;\nmov.s32 c, 16384;\n"
      "LAB_WAIT:\n"
      "mbarrier.try_wait.parity.shared::cta.b64 p, [%0], 0;\n"
      "add.s32 c, c, -1;\n"
      "setp.gt.and.s32 q, c, 0, !p;\n"
      "@q bra LAB_WAIT;\n}"
      ::"r"(bar) : "memory");
}
DEVI void tma4d(uint32_t dst, const void* tm, int c1, int c2, int c3, uint32_t bar) {
  asm volatile("cp.async.bulk.tensor.4d.shared::cluster.global.mbarrier::complete_tx::bytes [%0], [%1, {%3, %4, %5, %6}], [%2];"
               ::"r"(dst), "l"(tm), "r"(bar), "r"(0), "r"(c1), "r"(c2), "r"(c3) : "memory");
}
DEVI void prefetch_map(const void* tm) { asm volatile("prefetch.tensormap [%0];" ::"l"(tm) : "memory"); }
DEVI void bar_compute() { asm volatile("bar.sync 1, 256;" ::: "memory"); }
DEVI void bar_sync(int id, int n) { asm volatile("bar.sync %0, %1;" ::"r"(id), "r"(n) : "memory"); }
DEVI void bar_arrive(int id, int n) { asm volatile("bar.arrive %0, %1;" ::"r"(id), "r"(n) : "memory"); }
DEVI uint32_t gtime() { uint32_t t; asm volatile("mov.u32 %0, %%globaltimer_lo;" : "=r"(t)); return t; }
DEVI void fence_async_smem() { asm volatile("fence.proxy.async.shared::cta;" ::: "memory"); }
DEVI void ldsm4(uint32_t (&r)[4], uint32_t addr) {
  asm volatile("ldmatrix.sync.aligned.m8n8.x4.shared.b16 {%0,%1,%2,%3}, [%4];" : "=r"(r[0]), "=r"(r[1]), "=r"(r[2]), "=r"(r[3]) : "r"(addr) : "memory");
}
DEVI void ldsm4t(uint32_t (&r)[4], uint32_t addr) {
  asm volatile("ldmatrix.sync.aligned.m8n8.x4.trans.shared.b16 {%0,%1,%2,%3}, [%4];" : "=r"(r[0]), "=r"(r[1]), "=r"(r[2]), "=r"(r[3]) : "r"(addr) : "memory");
}
DEVI void stsm4t(uint32_t addr, uint32_t r0, uint32_t r1, uint32_t r2, uint32_t r3) {
  asm volatile("stmatrix.sync.aligned.m8n8.x4.trans.shared.b16 [%0], {%1,%2,%3,%4};" ::"r"(addr), "r"(r0), "r"(r1), "r"(r2), "r"(r3) : "memory");
}
DEVI void mma16816(float (&d)[4], const uint32_t (&a)[4], uint32_t b0, uint32_t b1) {
  asm volatile("mma.sync.aligned.m16n8k16.row.col.f32.bf16.bf16.f32 {%0,%1,%2,%3}, {%4,%5,%6,%7}, {%8,%9}, {%0,%1,%2,%3};"
               : "+f"(d[0]), "+f"(d[1]), "+f"(d[2]), "+f"(d[3])
               : "r"(a[0]), "r"(a[1]), "r"(a[2]), "r"(a[3]), "r"(b0), "r"(b1));
}
DEVI void mma16816z(float (&d)[4], const uint32_t (&a)[4], uint32_t b0, uint32_t b1) {
  asm volatile("mma.sync.aligned.m16n8k16.row.col.f32.bf16.bf16.f32 {%0,%1,%2,%3}, {%4,%5,%6,%7}, {%8,%9}, {%10,%10,%10,%10};"
               : "=f"(d[0]), "=f"(d[1]), "=f"(d[2]), "=f"(d[3])
               : "r"(a[0]), "r"(a[1]), "r"(a[2]), "r"(a[3]), "r"(b0), "r"(b1), "f"(0.f));
}
DEVI uint32_t lds32(uint32_t a) { uint32_t v; asm volatile("ld.shared.u32 %0, [%1];" : "=r"(v) : "r"(a) : "memory"); return v; }
DEVI float lds32f(uint32_t a) { float v; asm volatile("ld.shared.f32 %0, [%1];" : "=f"(v) : "r"(a) : "memory"); return v; }
DEVI float2 lds64f(uint32_t a) { float2 v; asm volatile("ld.shared.v2.f32 {%0,%1}, [%2];" : "=f"(v.x), "=f"(v.y) : "r"(a) : "memory"); return v; }
DEVI uint4 lds128(uint32_t a) { uint4 v; asm volatile("ld.shared.v4.u32 {%0,%1,%2,%3}, [%4];" : "=r"(v.x), "=r"(v.y), "=r"(v.z), "=r"(v.w) : "r"(a) : "memory"); return v; }
DEVI void sts16(uint32_t a, uint32_t v) { asm volatile("st.shared.u16 [%0], %1;" ::"r"(a), "h"((uint16_t)v) : "memory"); }
DEVI void sts32(uint32_t a, uint32_t v) { asm volatile("st.shared.u32 [%0], %1;" ::"r"(a), "r"(v) : "memory"); }
DEVI void sts32f(uint32_t a, float v) { asm volatile("st.shared.f32 [%0], %1;" ::"r"(a), "f"(v) : "memory"); }
DEVI void sts128(uint32_t a, uint4 v) { asm volatile("st.shared.v4.u32 [%0], {%1,%2,%3,%4};" ::"r"(a), "r"(v.x), "r"(v.y), "r"(v.z), "r"(v.w) : "memory"); }
DEVI uint4 ldg_poll128(const void* p) { uint4 v; asm volatile("ld.relaxed.gpu.global.v4.u32 {%0,%1,%2,%3}, [%4];" : "=r"(v.x), "=r"(v.y), "=r"(v.z), "=r"(v.w) : "l"(p) : "memory"); return v; }
DEVI uint32_t ldg_poll32(const void* p) { uint32_t v; asm volatile("ld.relaxed.gpu.global.u32 %0, [%1];" : "=r"(v) : "l"(p) : "memory"); return v; }
DEVI void stg_pub128(void* p, uint4 v) { asm volatile("st.relaxed.gpu.global.v4.u32 [%0], {%1,%2,%3,%4};" ::"l"(p), "r"(v.x), "r"(v.y), "r"(v.z), "r"(v.w) : "memory"); }
DEVI void stg_pub64(void* p, uint32_t x, uint32_t y) { asm volatile("st.relaxed.gpu.global.v2.u32 [%0], {%1,%2};" ::"l"(p), "r"(x), "r"(y) : "memory"); }
DEVI void stg_pub32(void* p, uint32_t x) { asm volatile("st.relaxed.gpu.global.u32 [%0], %1;" ::"l"(p), "r"(x) : "memory"); }
DEVI float ex2(float x) { float y; asm("ex2.approx.ftz.f32 %0, %1;" : "=f"(y) : "f"(x)); return y; }
DEVI uint32_t pack_bf16(float lo, float hi) { uint32_t r; asm("cvt.rn.bf16x2.f32 %0, %1, %2;" : "=r"(r) : "f"(hi), "f"(lo)); return r; }
DEVI float bf_lo(uint32_t w) { return __uint_as_float(w << 16); }
DEVI float bf_hi(uint32_t w) { return __uint_as_float(w & 0xffff0000u); }
DEVI uint32_t tagf(float v, uint32_t par) { return (__float_as_uint(v) & ~1u) | par; }
DEVI float asf(uint32_t u) { return __uint_as_float(u); }
DEVI uint32_t xand(uint32_t a, uint32_t b, uint32_t c) { uint32_t r; asm("lop3.b32 %0, %1, %2, %3, 0x42;" : "=r"(r) : "r"(a), "r"(b), "r"(c)); return r; }
DEVI bool ok4(const uint4& v, uint32_t npar) { return (xand(v.x, v.y, npar) & xand(v.z, v.w, npar) & 1u) != 0; }
DEVI float shx(float v, int m) { return __shfl_xor_sync(0xffffffffu, v, m); }

DEVI uint64_t make_desc(uint32_t addr, uint32_t sbo) {
  return (uint64_t)((addr & 0x3ffffu) >> 4) | (1ull << 16) | ((uint64_t)(sbo >> 4) << 32) | (1ull << 62);
}
template <bool ACC>
DEVI void wgmma_ss(float (&d)[16], uint64_t da, uint64_t db) {
  asm volatile(
      "{\n.reg .pred p;\nsetp.ne.b32 p, %18, 0;\n"
      "wgmma.mma_async.sync.aligned.m64n32k16.f32.bf16.bf16 "
      "{%0,%1,%2,%3,%4,%5,%6,%7,%8,%9,%10,%11,%12,%13,%14,%15}, %16, %17, p, 1, 1, 0, 0;\n}"
      : "+f"(d[0]), "+f"(d[1]), "+f"(d[2]), "+f"(d[3]), "+f"(d[4]), "+f"(d[5]), "+f"(d[6]), "+f"(d[7]), "+f"(d[8]),
        "+f"(d[9]), "+f"(d[10]), "+f"(d[11]), "+f"(d[12]), "+f"(d[13]), "+f"(d[14]), "+f"(d[15])
      : "l"(da), "l"(db), "n"(ACC ? 1 : 0));
}
template <bool ACC>
DEVI void wgmma_rs(float (&d)[16], const uint32_t (&a)[4], uint64_t db) {
  asm volatile(
      "{\n.reg .pred p;\nsetp.ne.b32 p, %21, 0;\n"
      "wgmma.mma_async.sync.aligned.m64n32k16.f32.bf16.bf16 "
      "{%0,%1,%2,%3,%4,%5,%6,%7,%8,%9,%10,%11,%12,%13,%14,%15}, {%16,%17,%18,%19}, %20, p, 1, 1, 0;\n}"
      : "+f"(d[0]), "+f"(d[1]), "+f"(d[2]), "+f"(d[3]), "+f"(d[4]), "+f"(d[5]), "+f"(d[6]), "+f"(d[7]), "+f"(d[8]),
        "+f"(d[9]), "+f"(d[10]), "+f"(d[11]), "+f"(d[12]), "+f"(d[13]), "+f"(d[14]), "+f"(d[15])
      : "r"(a[0]), "r"(a[1]), "r"(a[2]), "r"(a[3]), "l"(db), "n"(ACC ? 1 : 0));
}
DEVI void def_regs(float (&d)[16]) {
#pragma unroll
  for (int i = 0; i < 16; i++) asm volatile("" : "=f"(d[i])::"memory");
}
DEVI void fence_regs(float (&d)[16]) {
#pragma unroll
  for (int i = 0; i < 16; i++) asm volatile("" : "+f"(d[i])::"memory");
}
DEVI void wgmma_fence() { asm volatile("wgmma.fence.sync.aligned;" ::: "memory"); }
DEVI void wgmma_commit() { asm volatile("wgmma.commit_group.sync.aligned;" ::: "memory"); }
template <int N> DEVI void wgmma_wait() { asm volatile("wgmma.wait_group.sync.aligned %0;" ::"n"(N) : "memory"); }

DEVI void act_store_hilo(uint32_t a, float v0, float v1) {
  const uint32_t hi = pack_bf16(v0, v1);
  sts32(a, hi);
  sts32(a + 2 * ACT_STRIDE, pack_bf16(v0 - bf_lo(hi), v1 - bf_hi(hi)));
}
template <int N>
DEVI void poll_issue(uint4 (&v)[N], const char* p, uint32_t stride) {
  static_assert(N == 2 || N == 4, "");
  if constexpr (N == 4) {
    asm volatile(
        "ld.relaxed.gpu.global.v4.u32 {%0,%1,%2,%3}, [%16];\n"
        "ld.relaxed.gpu.global.v4.u32 {%4,%5,%6,%7}, [%17];\n"
        "ld.relaxed.gpu.global.v4.u32 {%8,%9,%10,%11}, [%18];\n"
        "ld.relaxed.gpu.global.v4.u32 {%12,%13,%14,%15}, [%19];"
        : "=r"(v[0].x), "=r"(v[0].y), "=r"(v[0].z), "=r"(v[0].w), "=r"(v[1].x), "=r"(v[1].y), "=r"(v[1].z), "=r"(v[1].w),
          "=r"(v[2].x), "=r"(v[2].y), "=r"(v[2].z), "=r"(v[2].w), "=r"(v[3].x), "=r"(v[3].y), "=r"(v[3].z), "=r"(v[3].w)
        : "l"(p), "l"(p + stride), "l"(p + 2 * stride), "l"(p + 3 * stride) : "memory");
  } else {
    asm volatile(
        "ld.relaxed.gpu.global.v4.u32 {%0,%1,%2,%3}, [%8];\n"
        "ld.relaxed.gpu.global.v4.u32 {%4,%5,%6,%7}, [%9];"
        : "=r"(v[0].x), "=r"(v[0].y), "=r"(v[0].z), "=r"(v[0].w), "=r"(v[1].x), "=r"(v[1].y), "=r"(v[1].z), "=r"(v[1].w)
        : "l"(p), "l"(p + stride) : "memory");
  }
}
DEVI void spin_clk(uint32_t n) {
  uint32_t c0, c;
  asm volatile("mov.u32 %0, %%clock;" : "=r"(c0) :: "memory");
  do { asm volatile("mov.u32 %0, %%clock;" : "=r"(c) :: "memory"); } while (c - c0 < n);
}
template <int N>
DEVI void poll_finish(uint4 (&r)[N], const char* p, uint32_t stride, uint32_t npar) {
  int it = kPollLimit;
  bool ok[N], all = true;
#pragma unroll
  for (int q = 0; q < N; q++) { ok[q] = ok4(r[q], npar); all = all && ok[q]; }
  while (!all && --it > 0) {
#pragma unroll
    for (int q = 0; q < N; q++) if (!ok[q]) r[q] = ldg_poll128(p + q * stride);
    all = true;
#pragma unroll
    for (int q = 0; q < N; q++) { ok[q] = ok4(r[q], npar); all = all && ok[q]; }
  }
}
DEVI void poll_pair(uint32_t& m0, uint32_t& m1, const float* p, uint32_t npar) {
  int it = kPollLimit;
  do { m0 = ldg_poll32(p); m1 = ldg_poll32(p + 32); } while (!__all_sync(0xffffffffu, ((m0 ^ npar) & (m1 ^ npar) & 1u) != 0) && --it > 0);
}
template <bool MAX>
DEVI float col_reduce(float (&v)[8], int lane) {
  const bool u16 = lane & 16, u8 = lane & 8, u4 = lane & 4;
#pragma unroll
  for (int q = 0; q < 4; q++) { const float a = u16 ? v[q] : v[q + 4], k = u16 ? v[q + 4] : v[q], o = shx(a, 16); v[q] = MAX ? fmaxf(k, o) : k + o; }
#pragma unroll
  for (int q = 0; q < 2; q++) { const float a = u8 ? v[q] : v[q + 2], k = u8 ? v[q + 2] : v[q], o = shx(a, 8); v[q] = MAX ? fmaxf(k, o) : k + o; }
  const float a = u4 ? v[0] : v[1], k = u4 ? v[1] : v[0], o = shx(a, 4);
  return MAX ? fmaxf(k, o) : k + o;
}

__global__ void __cluster_dims__(2, 1, 1) __launch_bounds__(NTHREADS, 1)
fused_kernel(const __nv_bfloat16* __restrict__ xin, __nv_bfloat16* __restrict__ out, const __nv_bfloat16* __restrict__ wq,
             Scratch* __restrict__ Gp, const __grid_constant__ Maps M) {
  extern __shared__ __align__(1024) uint8_t smem_raw[];
  const uint32_t sm = smem_u32(smem_raw);
  const int tid = threadIdx.x, cta = blockIdx.x;
  const int h = cta >> 2, j = cta & 3, pair = cta >> 1, rank = cta & 1;
  Scratch& G = *Gp;
  const int lane = tid & 31;
  auto bar = [&](int i) { return sm + SM_BAR + 8u * i; };
  const uint32_t epoch = ldg_poll32(&G.epoch[cta]);
  uint4 xu[2][2];
  uint2 xw[2];
  if (tid < 32) {
#pragma unroll
    for (int b = 0; b < 2; b++) {
      const __nv_bfloat16* xp = xin + b * 512 + lane * 16;
      asm volatile("ld.global.nc.v4.u32 {%0,%1,%2,%3}, [%4];" : "=r"(xu[b][0].x), "=r"(xu[b][0].y), "=r"(xu[b][0].z), "=r"(xu[b][0].w) : "l"(xp));
      asm volatile("ld.global.nc.v4.u32 {%0,%1,%2,%3}, [%4];" : "=r"(xu[b][1].x), "=r"(xu[b][1].y), "=r"(xu[b][1].z), "=r"(xu[b][1].w) : "l"(xp + 8));
      asm volatile("ld.global.nc.v2.u32 {%0,%1}, [%2];" : "=r"(xw[b].x), "=r"(xw[b].y) : "l"(xin + b * 512 + 128 * j + 4 * lane));
    }
  }
  if (tid < 256) {
    const int r0 = tid >> 4;
    const char* src = reinterpret_cast<const char*>(wq) + (size_t)(128 * j + r0) * 8192 + h * 256 + (tid & 15) * 16;
    const uint32_t dst = sm + SM_WQ + ((tid >> 3) & 1) * 8192 + r0 * 128 + (((tid & 7) ^ (r0 & 7)) << 4);
    asm volatile(
        "cp.async.cg.shared.global [%0], [%1], 16;\n"
        "cp.async.cg.shared.global [%0 + 2048], [%1 + 131072], 16;\n"
        "cp.async.cg.shared.global [%0 + 4096], [%1 + 262144], 16;\n"
        "cp.async.cg.shared.global [%0 + 6144], [%1 + 393216], 16;\n"
        "cp.async.cg.shared.global [%0 + 16384], [%1 + 524288], 16;\n"
        "cp.async.cg.shared.global [%0 + 18432], [%1 + 655360], 16;\n"
        "cp.async.cg.shared.global [%0 + 20480], [%1 + 786432], 16;\n"
        "cp.async.cg.shared.global [%0 + 22528], [%1 + 917504], 16;"
        ::"r"(dst), "l"(src) : "memory");
  }
  const uint32_t t_start = gtime();

  if (tid >= 256) {
    if (tid < 288) {
      if (lane == 0) {
#pragma unroll
        for (int i = 0; i < NBAR; i++) mbar_init(bar(i), i == BAR_R1FREE ? 8 : 1);
        asm volatile("fence.mbarrier_init.release.cluster;" ::: "memory");
        mbar_expect_tx(bar(BAR_S), 8192);
        mbar_expect_tx(bar(BAR_S + 1), 8192);
#pragma unroll
        for (int i = 0; i < 7; i++) prefetch_map(&M.m[i]);
      }
      __syncwarp();
      bar_arrive(2, NTHREADS);
      asm volatile("barrier.cluster.arrive.relaxed.aligned;" ::: "memory");
      const int p = lane;
      int mi = 0, c1 = 128 * j + 32 * (p & 3), c2 = 2 * h, c3 = 0, unit = 2 * (p + 1);
      uint32_t dst = SM_WUK + p * 8192u, bytes = 8192;
      if (p >= 4) { mi = 1; c1 = 0; c2 = 4 * rank + (((p - 4) >> 1) & 1) * 2; c3 = 16 * pair + ((p - 4) >> 2) * 8 + (p & 1) * 4; dst = SM_CKV + (p - 4) * 8192u; }
      if (p >= 12) { mi = p - 9; c1 = 128 * j; c2 = 3 * h; c3 = 0; dst = SM_G + (p - 12) * 12288u; bytes = 12288; unit = 3 * p - 9; }
      if (p >= 14) { mi = 2; c1 = 128 * j + 32 * (p - 14); c2 = 2 * h; dst = SM_WUV + (p - 14) * 8192u; bytes = 8192; unit = 2 * p + 4; }
      if (p == 18) { mi = 5; c1 = 48 * h; c2 = 2 * j; dst = SM_WD; bytes = 12288; unit = 41; }
      if (p >= 19) { mi = 6; c1 = 128 * h + 32 * (p - 19); c2 = 2 * j; dst = SM_WO + (p - 19) * 8192u; bytes = 8192; unit = 2 * p + 5; }
      const uint32_t t_issue = t_start + PACE_T0 + min(unit, 24) * PACE_DT1 + max(unit - 24, 0) * PACE_DT2 + (p >= PAUSE_AT ? PAUSE_NS : 0);
      const char* map = reinterpret_cast<const char*>(&M.m[0]) + 128 * mi;
      const uint32_t mybar = bar(p);
      dst += sm;
#pragma unroll 1
      for (int q = 0; q < NPIECE; q++) {
        if (q >= WINDOW) mbar_wait(bar(q - WINDOW));
        if (q == BAR_G) mbar_wait(bar(BAR_R1FREE));
        const uint32_t tq = __shfl_sync(0xffffffffu, t_issue, q);
        int guard = 1 << 16;
        while ((int)(gtime() - tq) < 0 && --guard > 0) {}
        if (lane == q) { mbar_expect_tx(mybar, bytes); tma4d(dst, map, c1, c2, c3, mybar); }
      }
      return;
    }
    asm volatile("barrier.cluster.arrive.relaxed.aligned;" ::: "memory");
    const int oidx = ((lane >> 2) & 1) * 512 + 128 * j + 4 * h + (lane & 3);
    const float xres = __bfloat162float(xin[oidx]);
    const uint32_t par = (epoch + 1u) & 1u, npar = par ^ 1u;
    {
      const uint4 inv = make_uint4(npar, npar, npar, npar);
      uint4* q = reinterpret_cast<uint4*>(&G.x0[cta][0]) + lane;
      stg_pub128(q, inv);
      stg_pub128(q + 32, inv);
      stg_pub128(reinterpret_cast<uint4*>(&G.qlat[lane >> 4][j >> 1][h][(j & 1) * 64]) + (lane & 15), inv);
      bar_arrive(2, NTHREADS);
      q = reinterpret_cast<uint4*>(&G.x2[cta][0]) + lane;
      stg_pub128(q, inv);
      stg_pub128(q + 32, inv);
      q = reinterpret_cast<uint4*>(&G.x3[j][h][0]) + lane;
      stg_pub128(q, inv);
      stg_pub128(q + 32, inv);
      q = reinterpret_cast<uint4*>(&G.xd[cta][0]) + lane;
      stg_pub128(q, inv);
      if (lane < 16) stg_pub128(q + 32, inv);
      if (rank == 0) { stg_pub32(&G.mx[lane][pair], npar); stg_pub32(&G.ls[lane][pair], npar); }
      bar_arrive(3, 288);
      q = reinterpret_cast<uint4*>(&G.part[pair][rank][0][0][0]) + lane;
#pragma unroll 1
      for (int i = 0; i < 32; i++) {
        int guard = 1 << 16;
        while ((int)(gtime() - (t_start + PRE_T0 + i * PRE_DT)) < 0 && --guard > 0) {}
        stg_pub128(q + 32 * ((i & 7) + ((i >> 3) & 1) * 16 + (i >> 4) * 8), inv);
      }
      asm volatile("fence.proxy.async.global;" ::: "memory");
      __syncwarp();
#pragma unroll
      for (int b = 0; b < 4; b++) {
        const int w = b & 1, half = b >> 1;
        bar_sync((half ? 11 : 4) + w, 160);
        if (lane == 0) {
          fence_async_smem();
          asm volatile("cp.async.bulk.global.shared::cta.bulk_group [%0], [%1], %2;"
                       ::"l"(&G.part[pair][rank][w * 2 + half][0][0]), "r"(sm + SM_QB + w * 8192 + half * 4096), "r"(4096) : "memory");
          asm volatile("cp.async.bulk.commit_group;" ::: "memory");
        }
      }
    }
    {
      uint32_t m0, m1;
      bar_sync(6, 288);
      if (rank == 0) {
        float l = lds32f(sm + SM_WSUM + lane * 4);
#pragma unroll
        for (int w = 1; w < 8; w++) l += lds32f(sm + SM_WSUM + w * 128 + lane * 4);
        stg_pub32(&G.ls[lane][pair], tagf(l, par));
      }
      poll_pair(m0, m1, &G.mx[h][lane], npar);
      float x0 = asf(m0), x1 = asf(m1);
#pragma unroll
      for (int o = 16; o > 0; o >>= 1) { x0 = fmaxf(x0, shx(x0, o)); x1 = fmaxf(x1, shx(x1, o)); }
      const uint32_t wb = pack_bf16(ex2(asf(m0) - x0), ex2(asf(m1) - x1));
      sts16(sm + ACT_W + lane * 2, wb);
      sts16(sm + ACT_W + 64 + lane * 2, 0);
      sts16(sm + ACT_W + ACT_STRIDE + lane * 2, 0);
      sts16(sm + ACT_W + ACT_STRIDE + 64 + lane * 2, wb >> 16);
      bar_arrive(7, 288);
      spin_clk(M_DELAY);
      poll_pair(m0, m1, &G.ls[h][lane], npar);
      x0 = bf_lo(wb) * asf(m0);
      x1 = bf_hi(wb) * asf(m1);
#pragma unroll
      for (int o = 16; o > 0; o >>= 1) { x0 += shx(x0, o); x1 += shx(x1, o); }
      if (lane == 0) { sts32f(sm + SM_INVL, 1.f / x0); sts32f(sm + SM_INVL + 4, 1.f / x1); }
      uint4 u[2][4];
      const char* src = reinterpret_cast<const char*>(&G.xd[4 * h][4 * lane]);
      const char* src2 = reinterpret_cast<const char*>(&G.xd[4 * h][128 + 4 * (lane & 15)]);
      int it = kPollLimit;
      bool ok;
      do {
        poll_issue<4>(u[0], src, 768);
        poll_issue<4>(u[1], src2, 768);
        ok = true;
#pragma unroll
        for (int q = 0; q < 4; q++) ok = ok && ok4(u[0][q], npar) && ok4(u[1][q], npar);
      } while (!__all_sync(0xffffffffu, ok) && --it > 0);
#pragma unroll
      for (int e = 0; e < 2; e++) {
        const uint4 (&w)[4] = u[e];
        const float s0 = asf(w[0].x) + asf(w[1].x) + (asf(w[2].x) + asf(w[3].x)), s1 = asf(w[0].y) + asf(w[1].y) + (asf(w[2].y) + asf(w[3].y));
        const float s2 = asf(w[0].z) + asf(w[1].z) + (asf(w[2].z) + asf(w[3].z)), s3 = asf(w[0].w) + asf(w[1].w) + (asf(w[2].w) + asf(w[3].w));
        const uint32_t hh = pack_bf16(__fdividef(s2, 1.f + __expf(-s0)), __fdividef(s3, 1.f + __expf(-s1)));
        if (e == 0 || lane < 16) {
          sts16(sm + ACT_H + 2 * (32 * e + lane), hh);
          sts16(sm + ACT_H + ACT_STRIDE + 2 * (32 * e + lane), hh >> 16);
        }
      }
      bar_arrive(8, 288);
    }
    {
      const float* src = &G.x3[j][lane >> 2][8 * h + 2 * (lane & 3)];
      const size_t hs = 8 * (&G.x3[0][1][0] - &G.x3[0][0][0]);
      uint32_t x[8];
      bar_sync(9, 288);
      spin_clk(X3_DELAY);
      int it = kPollLimit;
      bool ok;
      do {
        asm volatile(
            "ld.relaxed.gpu.global.v2.u32 {%0,%1}, [%8];\n"
            "ld.relaxed.gpu.global.v2.u32 {%2,%3}, [%9];\n"
            "ld.relaxed.gpu.global.v2.u32 {%4,%5}, [%10];\n"
            "ld.relaxed.gpu.global.v2.u32 {%6,%7}, [%11];"
            : "=r"(x[0]), "=r"(x[1]), "=r"(x[2]), "=r"(x[3]), "=r"(x[4]), "=r"(x[5]), "=r"(x[6]), "=r"(x[7])
            : "l"(src), "l"(src + hs), "l"(src + 2 * hs), "l"(src + 3 * hs) : "memory");
        ok = (((x[0] ^ npar) & (x[1] ^ npar) & (x[2] ^ npar) & (x[3] ^ npar) & (x[4] ^ npar) & (x[5] ^ npar) & (x[6] ^ npar) & (x[7] ^ npar)) & 1u) != 0;
      } while (!ok && --it > 0);
      __syncwarp();
      const float s0 = asf(x[0]) + asf(x[2]) + (asf(x[4]) + asf(x[6])), s1 = asf(x[1]) + asf(x[3]) + (asf(x[5]) + asf(x[7]));
      float r = ((lane & 4) ? s1 : s0) + shx((lane & 4) ? s0 : s1, 4);
      r += shx(r, 8);
      r += shx(r, 16);
      if (lane < 8) out[oidx] = __float2bfloat16(xres + r);
      if (lane == 0) { G.epoch[cta] = epoch + 1; asm volatile("cp.async.bulk.wait_group 0;" ::: "memory"); }
    }
    return;
  }

  const int warp = tid >> 5;
  const int g = lane >> 2, t = lane & 3;
  if (warp == 0) {
      const uint4 (&u)[2][2] = xu;
      float s[2], ss[2];
#pragma unroll
      for (int b = 0; b < 2; b++) {
        const uint32_t w[8] = {u[b][0].x, u[b][0].y, u[b][0].z, u[b][0].w, u[b][1].x, u[b][1].y, u[b][1].z, u[b][1].w};
        s[b] = 0.f;
#pragma unroll
        for (int q = 0; q < 8; q++) s[b] += bf_lo(w[q]) + bf_hi(w[q]);
      }
#pragma unroll
      for (int o = 16; o > 0; o >>= 1) { s[0] += shx(s[0], o); s[1] += shx(s[1], o); }
#pragma unroll
      for (int b = 0; b < 2; b++) {
        const uint32_t w[8] = {u[b][0].x, u[b][0].y, u[b][0].z, u[b][0].w, u[b][1].x, u[b][1].y, u[b][1].z, u[b][1].w};
        s[b] *= 1.f / 512.f;
        ss[b] = 0.f;
#pragma unroll
        for (int q = 0; q < 8; q++) { const float d0 = bf_lo(w[q]) - s[b], d1 = bf_hi(w[q]) - s[b]; ss[b] += d0 * d0 + d1 * d1; }
      }
#pragma unroll
      for (int o = 16; o > 0; o >>= 1) { ss[0] += shx(ss[0], o); ss[1] += shx(ss[1], o); }
#pragma unroll
      for (int b = 0; b < 2; b++) {
        const float r = rsqrtf(ss[b] * (1.f / 512.f) + 1e-5f);
        act_store_hilo(sm + ACT_X + b * ACT_STRIDE + 8 * lane, (bf_lo(xw[b].x) - s[b]) * r, (bf_hi(xw[b].x) - s[b]) * r);
        act_store_hilo(sm + ACT_X + b * ACT_STRIDE + 8 * lane + 4, (bf_lo(xw[b].y) - s[b]) * r, (bf_hi(xw[b].y) - s[b]) * r);
      }
    }
  const uint32_t par = (epoch + 1u) & 1u, npar = par ^ 1u;
  asm volatile("cp.async.wait_all;" ::: "memory");
  bar_sync(2, NTHREADS);
  const int mat = lane >> 3, l7 = lane & 7;
  const int tr_row = l7 + (mat >> 1) * 8;
  const uint32_t tr_off = sm + tr_row * 128 + ((((warp & 3) * 2 + (mat & 1)) ^ l7) << 4);
  const uint32_t tr_cb = warp >> 2;
  const uint32_t bf4 = sm + (l7 & 3) * ACT_STRIDE + mat * 16;
  const uint32_t bf2 = sm + (l7 & 1) * ACT_STRIDE + mat * 16;

  {
    float d[4], e[4];
    uint32_t b[4][4], a[8][4];
#pragma unroll
    for (int q = 0; q < 4; q++) ldsm4(b[q], bf4 + ACT_X + 64 * q);
#pragma unroll
    for (int s = 0; s < 8; s++) ldsm4t(a[s], tr_off + SM_WQ + (s >> 2) * 16384 + tr_cb * 8192 + (s & 3) * 2048);
    mma16816z(d, a[0], b[0][0], b[0][1]);
    mma16816z(e, a[1], b[0][2], b[0][3]);
#pragma unroll
    for (int q = 1; q < 4; q++) { mma16816(d, a[2 * q], b[q][0], b[q][1]); mma16816(e, a[2 * q + 1], b[q][2], b[q][3]); }
    float r0 = d[0] + e[0], r1 = d[1] + e[1], r2 = d[2] + e[2], r3 = d[3] + e[3];
    const float k0 = (t & 1) ? r2 : r0, k1 = (t & 1) ? r3 : r1, s0 = (t & 1) ? r0 : r2, s1 = (t & 1) ? r1 : r3;
    r0 = k0 + shx(s0, 1); r1 = k1 + shx(s1, 1);
    if (t < 2) stg_pub64(&G.x0[cta][(16 * warp + g + 8 * t) * 2], tagf(r0, par), tagf(r1, par));
  }
  if (tid < 64) {
    uint4 v[4];
    mbar_wait(bar(BAR_WUK + X0_PIECE));
    poll_issue<4>(v, reinterpret_cast<const char*>(&G.x0[4 * h][4 * tid]), 1024);
    poll_finish<4>(v, reinterpret_cast<const char*>(&G.x0[4 * h][4 * tid]), 1024, npar);
    const float sc = 0.08838834764831845f * 1.4426950408889634f;
    act_store_hilo(sm + ACT_Q + 4 * tid, (asf(v[0].x) + asf(v[1].x) + asf(v[2].x) + asf(v[3].x)) * sc, (asf(v[0].z) + asf(v[1].z) + asf(v[2].z) + asf(v[3].z)) * sc);
    act_store_hilo(sm + ACT_Q + ACT_STRIDE + 4 * tid, (asf(v[0].y) + asf(v[1].y) + asf(v[2].y) + asf(v[3].y)) * sc, (asf(v[0].w) + asf(v[1].w) + asf(v[2].w) + asf(v[3].w)) * sc);
  }
  bar_compute();
  {
    float d[4], e[4];
    const int row = (warp & 1) * 16 + l7 + (mat & 1) * 8;
    uint32_t b[4][4];
#pragma unroll
    for (int q = 0; q < 4; q++) ldsm4(b[q], bf4 + ACT_Q + 64 * q);
    mbar_wait(bar(BAR_WUK + (warp >> 1)));
    const uint32_t abase = sm + SM_WUK + (warp >> 1) * 8192 + row * 128;
#pragma unroll
    for (int q = 0; q < 4; q++) {
      uint32_t a0[4], a1[4];
      ldsm4(a0, abase + (q >> 1) * 4096 + ((((q & 1) * 4 + (mat >> 1)) ^ l7) << 4));
      ldsm4(a1, abase + (q >> 1) * 4096 + ((((q & 1) * 4 + 2 + (mat >> 1)) ^ l7) << 4));
      if (q == 0) { mma16816z(d, a0, b[0][0], b[0][1]); mma16816z(e, a1, b[0][2], b[0][3]); }
      else { mma16816(d, a0, b[q][0], b[q][1]); mma16816(e, a1, b[q][2], b[q][3]); }
    }
    float r0 = d[0] + e[0], r1 = d[1] + e[1], r2 = d[2] + e[2], r3 = d[3] + e[3];
    const float k0 = (t & 1) ? r2 : r0, k1 = (t & 1) ? r3 : r1, s0 = (t & 1) ? r0 : r2, s1 = (t & 1) ? r1 : r3;
    r0 = k0 + shx(s0, 1); r1 = k1 + shx(s1, 1);
    sts32f(sm + SM_QST + (t >> 1) * 512 + (16 * warp + g + 8 * (t & 1)) * 4, (t & 2) ? r1 : r0);
    __syncwarp();
    if (lane == 0) mbar_arrive(bar(BAR_R1FREE));
    asm volatile("barrier.cluster.arrive.relaxed.aligned;" ::: "memory");
    bar_compute();
    if (tid < 128) {
      const float2 v = lds64f(sm + SM_QST + tid * 8);
      stg_pub32(&G.qlat[tid >> 6][j >> 1][h][(j & 1) * 64 + (tid & 63)], (pack_bf16(v.x, v.y) & ~1u) | par);
    }
  }
  {
    mbar_wait(bar(BAR_CKV + XQ_PIECE));
    uint4 v[4];
    poll_issue<4>(v, reinterpret_cast<const char*>(&G.qlat[pair >> 5][rank][0][0]) + tid * 16, 4096);
    poll_finish<4>(v, reinterpret_cast<const char*>(&G.qlat[pair >> 5][rank][0][0]) + tid * 16, 4096, npar);
    const int hh = tid >> 5, pc = tid & 31;
    const uint32_t dst = sm + SM_QB + (pc >> 3) * 4096 + hh * 128 + (((pc & 7) ^ (hh & 7)) << 4);
#pragma unroll
    for (int i = 0; i < 4; i++) sts128(dst + i * 1024, make_uint4(v[i].x & ~1u, v[i].y & ~1u, v[i].z & ~1u, v[i].w & ~1u));
    fence_async_smem();
    asm volatile("barrier.cluster.wait.aligned;" ::: "memory");
    bar_sync(3, 288);
  }
  const int wg = warp >> 2, wq4 = warp & 3;
  float s[16];
  uint32_t pa[16][4];
  def_regs(s);
  {
    const uint64_t da = make_desc(sm + SM_CKV + wg * 32768, 2048), db = make_desc(sm + SM_QB, 1024);
    const uint32_t pbase = sm + SM_CKV + wg * 16384 + (mat >> 1) * 2048 + l7 * 128 + (((wq4 * 2 + (mat & 1)) ^ l7) << 4);
#pragma unroll
    for (int cp = 0; cp < 2; cp++) {
      mbar_wait(bar(BAR_CKV + wg * 4 + cp * 2));
      mbar_wait(bar(BAR_CKV + wg * 4 + cp * 2 + 1));
      wgmma_fence();
#pragma unroll
      for (int k = 0; k < 8; k++) {
        const int blk = k >> 2, ks = k & 3;
        if (cp == 0 && k == 0) wgmma_ss<false>(s, da, db);
        else wgmma_ss<true>(s, da + ((cp * 16384 + blk * 1024 + ks * 32) >> 4), db + (((cp * 2 + blk) * 4096 + ks * 32) >> 4));
      }
      wgmma_commit();
      if (cp == 0) {
        mbar_wait(bar(BAR_CKV + wg * 2));
        mbar_wait(bar(BAR_CKV + wg * 2 + 1));
#pragma unroll
        for (int q = 0; q < 8; q++) ldsm4t(pa[(q >> 2) * 8 + (q & 3)], pbase + (q >> 2) * 1024 + (q & 3) * 4096);
      }
    }
    uint32_t rdst, rbar;
    asm volatile("mapa.shared::cluster.u32 %0, %1, %2;" : "=r"(rdst) : "r"(sm + SM_SRECV + tid * 16), "r"(rank ^ 1));
    asm volatile("mapa.shared::cluster.u32 %0, %1, %2;" : "=r"(rbar) : "r"(bar(BAR_S + wg)), "r"(rank ^ 1));
    wgmma_wait<0>();
    fence_regs(s);
#pragma unroll
    for (int q = 0; q < 4; q++)
      asm volatile("st.async.weak.shared::cluster.mbarrier::complete_tx::bytes.v4.f32 [%0], {%1,%2,%3,%4}, [%5];"
                   ::"r"(rdst + q * 4096), "f"(s[4 * q]), "f"(s[4 * q + 1]), "f"(s[4 * q + 2]), "f"(s[4 * q + 3]), "r"(rbar) : "memory");
    mbar_wait(bar(BAR_CKV + 4 + wg * 2));
    mbar_wait(bar(BAR_CKV + 4 + wg * 2 + 1));
#pragma unroll
    for (int q = 0; q < 8; q++) ldsm4t(pa[(q >> 2) * 8 + 4 + (q & 3)], pbase + 32768 + (q >> 2) * 1024 + (q & 3) * 4096);
    mbar_wait(bar(BAR_S + wg));
#pragma unroll
    for (int q = 0; q < 4; q++) {
      const uint4 o = lds128(sm + SM_SRECV + tid * 16 + q * 4096);
      s[4 * q] += asf(o.x); s[4 * q + 1] += asf(o.y); s[4 * q + 2] += asf(o.z); s[4 * q + 3] += asf(o.w);
    }
  }
  const int mycol = ((lane >> 3) & 3) * 8 + (lane & 3) * 2 + ((lane >> 2) & 1);
  {
    float v[8];
#pragma unroll
    for (int i = 0; i < 4; i++) { v[2 * i] = fmaxf(s[4 * i], s[4 * i + 2]); v[2 * i + 1] = fmaxf(s[4 * i + 1], s[4 * i + 3]); }
    sts32f(sm + SM_WMAX + warp * 128 + mycol * 4, col_reduce<true>(v, lane));
    bar_compute();
    float m = lds32f(sm + SM_WMAX + mycol * 4);
#pragma unroll
    for (int w = 1; w < 8; w++) m = fmaxf(m, lds32f(sm + SM_WMAX + w * 128 + mycol * 4));
    if (tid < 32 && rank == 0) stg_pub32(&G.mx[mycol][pair], tagf(m, par));
    m = asf(tagf(m, par));
#pragma unroll
    for (int i = 0; i < 4; i++) {
      const float m0 = __shfl_sync(0xffffffffu, m, (i << 3) | t), m1 = __shfl_sync(0xffffffffu, m, (i << 3) | 4 | t);
      s[4 * i] = ex2(s[4 * i] - m0); s[4 * i + 1] = ex2(s[4 * i + 1] - m1);
      s[4 * i + 2] = ex2(s[4 * i + 2] - m0); s[4 * i + 3] = ex2(s[4 * i + 3] - m1);
    }
#pragma unroll
    for (int c2 = 0; c2 < 2; c2++) {
      const int i = 2 * c2 + (mat >> 1), hh = 8 * i + l7, kc = wq4 * 2 + (mat & 1);
      stsm4t(sm + SM_P + wg * 4096 + hh * 128 + ((kc ^ l7) << 4),
             pack_bf16(s[8 * c2], s[8 * c2 + 1]), pack_bf16(s[8 * c2 + 2], s[8 * c2 + 3]),
             pack_bf16(s[8 * c2 + 4], s[8 * c2 + 5]), pack_bf16(s[8 * c2 + 6], s[8 * c2 + 7]));
    }
    fence_async_smem();
    bar_compute();
  }
  {
    float o0[16], o1[16];
    def_regs(o0);
    def_regs(o1);
    const uint64_t db = make_desc(sm + SM_P, 1024);
    const uint32_t am = (g & 1) ? 0xffffffffu : 0xfffefffeu, om = (g & 1) ? 0u : par * 0x10001u;
    const uint32_t st0 = sm + SM_QB + wg * 8192 + (8 * (mat >> 1) + l7) * 128 + (((wq4 * 2 + (mat & 1)) ^ l7) << 4);
    auto stage = [&](float (&o)[16], int half) {
      fence_regs(o);
#pragma unroll
      for (int c2 = 0; c2 < 2; c2++)
        stsm4t(st0 + half * 4096 + c2 * 2048, (pack_bf16(o[8 * c2], o[8 * c2 + 1]) & am) | om, (pack_bf16(o[8 * c2 + 2], o[8 * c2 + 3]) & am) | om,
               (pack_bf16(o[8 * c2 + 4], o[8 * c2 + 5]) & am) | om, (pack_bf16(o[8 * c2 + 6], o[8 * c2 + 7]) & am) | om);
      bar_arrive((half ? 11 : 4) + wg, 160);
    };
    wgmma_fence();
#pragma unroll
    for (int k = 0; k < 8; k++) {
      if (k == 0) wgmma_rs<false>(o0, pa[0], db);
      else wgmma_rs<true>(o0, pa[k], db + (((k >> 2) * 4096 + (k & 3) * 32) >> 4));
    }
    wgmma_commit();
#pragma unroll
    for (int k = 0; k < PV_PRE; k++) {
      if (k == 0) wgmma_rs<false>(o1, pa[8], db);
      else wgmma_rs<true>(o1, pa[8 + k], db + (((k >> 2) * 4096 + (k & 3) * 32) >> 4));
    }
    wgmma_commit();
    wgmma_wait<1>();
    stage(o0, 0);
    wgmma_fence();
#pragma unroll
    for (int k = PV_PRE; k < 8; k++) wgmma_rs<true>(o1, pa[8 + k], db + (((k >> 2) * 4096 + (k & 3) * 32) >> 4));
    wgmma_commit();
    wgmma_wait<0>();
    stage(o1, 1);
    {
      float v[8];
#pragma unroll
      for (int i = 0; i < 4; i++) { v[2 * i] = s[4 * i] + s[4 * i + 2]; v[2 * i + 1] = s[4 * i + 1] + s[4 * i + 3]; }
      sts32f(sm + SM_WSUM + warp * 128 + mycol * 4, col_reduce<false>(v, lane));
      bar_arrive(6, 288);
    }
  }
  if (warp < 6) {
    const int m2 = warp >= 3, tile = warp - 3 * m2;
    float d[4], e[4];
    uint32_t b[4][4];
#pragma unroll
    for (int q = 0; q < 4; q++) ldsm4(b[q], bf4 + ACT_X + 64 * q);
    mbar_wait(bar(BAR_G + m2));
    const uint32_t abase = sm + SM_G + m2 * 12288 + tile * 4096 + tr_row * 32 + (((mat & 1) ^ ((tr_row >> 2) & 1)) << 4);
#pragma unroll
    for (int q = 0; q < 4; q++) {
      uint32_t a0[4], a1[4];
      ldsm4t(a0, abase + q * 1024);
      ldsm4t(a1, abase + q * 1024 + 512);
      if (q == 0) { mma16816z(d, a0, b[0][0], b[0][1]); mma16816z(e, a1, b[0][2], b[0][3]); }
      else { mma16816(d, a0, b[q][0], b[q][1]); mma16816(e, a1, b[q][2], b[q][3]); }
    }
    float r0 = d[0] + e[0], r1 = d[1] + e[1], r2 = d[2] + e[2], r3 = d[3] + e[3];
    const float k0 = (t & 1) ? r2 : r0, k1 = (t & 1) ? r3 : r1, s0 = (t & 1) ? r0 : r2, s1 = (t & 1) ? r1 : r3;
    r0 = k0 + shx(s0, 1); r1 = k1 + shx(s1, 1);
    if (t < 2) stg_pub64(&G.xd[cta][(16 * tile + g + 8 * t) * 4 + 2 * m2], tagf(r0, par), tagf(r1, par));
  }
  uint32_t wf[8][4];
  {
    const int rg = (tid & 127) >> 3, pc = (tid & 7) + 8 * wg;
    uint4 v[4];
    const char* src = reinterpret_cast<const char*>(&G.part[rg][j >> 1][(j & 1) * 2 + wg][h][0]) + (((pc & 7) ^ (h & 7)) << 4);
    {
      const uint32_t dmax = wg == 0 ? X1_DELAY : X1_DELAY_B, dmin = wg == 0 ? X1_MIN : X1_MIN_B, tx = t_start + (wg == 0 ? X1_T : X1_T_B);
      uint32_t c0, c;
      asm volatile("mov.u32 %0, %%clock;" : "=r"(c0) :: "memory");
      do { asm volatile("mov.u32 %0, %%clock;" : "=r"(c) :: "memory"); } while (c - c0 < dmax && (c - c0 < dmin || (int)(gtime() - tx) < 0));
    }
    poll_issue<4>(v, src, 16 * 32768);
#pragma unroll
    for (int q = 0; q < 4; q++) mbar_wait(bar(BAR_WUV + q));
#pragma unroll
    for (int q = 0; q < 8; q++) ldsm4t(wf[q], tr_off + SM_WUV + (q >> 1) * 8192 + tr_cb * 4096 + (q & 1) * 2048);
    poll_finish<4>(v, src, 16 * 32768, npar);
    const uint32_t dst = sm + SM_CKV + (pc >> 3) * 8192 + rg * 128 + (((pc & 7) ^ (rg & 7)) << 4);
#pragma unroll
    for (int i = 0; i < 4; i++) sts128(dst + i * 2048, make_uint4(v[i].x & ~1u, v[i].y & ~1u, v[i].z & ~1u, v[i].w & ~1u));
    bar_sync(7, 288);
    float d[4], e[4];
    uint32_t b[2][4], a[4][4];
    ldsm4(b[0], bf2 + ACT_W);
    ldsm4(b[1], bf2 + ACT_W + 64);
#pragma unroll
    for (int s4 = 0; s4 < 4; s4++) ldsm4t(a[s4], tr_off + SM_CKV + tr_cb * 8192 + s4 * 2048);
    mma16816z(d, a[0], b[0][0], b[0][1]);
    mma16816z(e, a[1], b[0][2], b[0][3]);
    mma16816(d, a[2], b[1][0], b[1][1]);
    mma16816(e, a[3], b[1][2], b[1][3]);
    const float val = (t & 2) ? ((t & 1) ? d[3] + e[3] : d[2] + e[2]) : ((t & 1) ? d[1] + e[1] : d[0] + e[0]);
    sts16(sm + ACT_CL + (t & 1) * ACT_STRIDE + (16 * warp + g + 8 * (t >> 1)) * 2, pack_bf16(val, 0.f));
    bar_compute();
  }
  {
    float d[4][4];
    uint32_t b[4][4];
#pragma unroll
    for (int q = 0; q < 4; q++) ldsm4(b[q], bf2 + ACT_CL + 64 * q);
#pragma unroll
    for (int q = 0; q < 4; q++) mma16816z(d[q], wf[2 * q], b[q][0], b[q][1]);
#pragma unroll
    for (int q = 0; q < 4; q++) mma16816(d[q], wf[2 * q + 1], b[q][2], b[q][3]);
    const int o = (t & 1) * 2;
    const float r0 = o ? d[0][2] + d[1][2] + (d[2][2] + d[3][2]) : d[0][0] + d[1][0] + (d[2][0] + d[3][0]);
    const float r1 = o ? d[0][3] + d[1][3] + (d[2][3] + d[3][3]) : d[0][1] + d[1][1] + (d[2][1] + d[3][1]);
    if (t < 2) stg_pub64(&G.x2[cta][(16 * warp + g + 8 * t) * 2], tagf(r0, par), tagf(r1, par));
  }
  uint32_t wd[3][4];
  {
    uint4 v[4];
    const char* src = reinterpret_cast<const char*>(&G.x2[4 * h][4 * tid]);
    if (tid < 64) {
      uint32_t c0, c;
      asm volatile("mov.u32 %0, %%clock;" : "=r"(c0) :: "memory");
      do { asm volatile("mov.u32 %0, %%clock;" : "=r"(c) :: "memory"); } while (c - c0 < X2_DELAY && (c - c0 < X2_MIN || (int)(gtime() - (t_start + X2_T)) < 0));
      poll_issue<4>(v, src, 1024);
    }
    mbar_wait(bar(BAR_WD));
#pragma unroll
    for (int s3 = 0; s3 < 3; s3++) ldsm4t(wd[s3], tr_off + SM_WD + tr_cb * 6144 + s3 * 2048);
#pragma unroll
    for (int p = 0; p < 3; p++) {
      mbar_wait(bar(BAR_WO + p));
      ldsm4t(wf[2 * p], tr_off + SM_WO + p * 8192 + tr_cb * 4096);
      ldsm4t(wf[2 * p + 1], tr_off + SM_WO + p * 8192 + tr_cb * 4096 + 2048);
    }
    if (tid < 64) {
      poll_finish<4>(v, src, 1024, npar);
      const float s0 = asf(v[0].x) + asf(v[1].x) + (asf(v[2].x) + asf(v[3].x)), s1 = asf(v[0].y) + asf(v[1].y) + (asf(v[2].y) + asf(v[3].y));
      const float s2 = asf(v[0].z) + asf(v[1].z) + (asf(v[2].z) + asf(v[3].z)), s3 = asf(v[0].w) + asf(v[1].w) + (asf(v[2].w) + asf(v[3].w));
      sts32(sm + ACT_CTX + 4 * tid, pack_bf16(s0, s2));
      sts32(sm + ACT_CTX + ACT_STRIDE + 4 * tid, pack_bf16(s1, s3));
    }
    mbar_wait(bar(BAR_WO + 3));
    ldsm4t(wf[6], tr_off + SM_WO + 3 * 8192 + tr_cb * 4096);
    ldsm4t(wf[7], tr_off + SM_WO + 3 * 8192 + tr_cb * 4096 + 2048);
  }
  bar_sync(8, 288);
  {
    float d[4], e[4], f[4];
    uint32_t b[4][4], bh[2][4];
#pragma unroll
    for (int q = 0; q < 4; q++) ldsm4(b[q], bf2 + ACT_CTX + 64 * q);
    ldsm4(bh[0], bf2 + ACT_H);
    ldsm4(bh[1], bf2 + ACT_H + 64);
    const float2 il = lds64f(sm + SM_INVL);
    mma16816z(d, wf[0], b[0][0], b[0][1]);
    mma16816z(e, wf[1], b[0][2], b[0][3]);
    mma16816z(f, wd[0], bh[0][0], bh[0][1]);
#pragma unroll
    for (int p = 1; p < 4; p++) {
      mma16816(d, wf[2 * p], b[p][0], b[p][1]);
      mma16816(e, wf[2 * p + 1], b[p][2], b[p][3]);
      if (p == 1) mma16816(f, wd[1], bh[0][2], bh[0][3]);
      if (p == 2) mma16816(f, wd[2], bh[1][0], bh[1][1]);
    }
    const float r0 = (t & 1) ? (d[2] + e[2]) * il.x + f[2] : (d[0] + e[0]) * il.x + f[0];
    const float r1 = (t & 1) ? (d[3] + e[3]) * il.y + f[3] : (d[1] + e[1]) * il.y + f[1];
    if (t < 2) stg_pub64(&G.x3[j][h][(16 * warp + g + 8 * t) * 2], tagf(r0, par), tagf(r1, par));
  }
  bar_arrive(9, 288);
}

typedef CUresult (*EncodeFn)(CUtensorMap*, CUtensorMapDataType, cuuint32_t, void*, const cuuint64_t*, const cuuint64_t*,
                             const cuuint32_t*, const cuuint32_t*, CUtensorMapInterleave, CUtensorMapSwizzle,
                             CUtensorMapL2promotion, CUtensorMapFloatOOBfill);

static void make_map(EncodeFn enc, CUtensorMap* m, const void* base, uint64_t inner, uint64_t d1, uint64_t s1, uint64_t d2,
                     uint64_t s2, uint64_t d3, uint64_t s3, uint32_t b1, uint32_t b2, uint32_t b3, CUtensorMapSwizzle sw) {
  cuuint64_t dims[4] = {inner, d1, d2, d3};
  cuuint64_t strides[3] = {s1, s2, s3};
  cuuint32_t box[4] = {(cuuint32_t)inner, b1, b2, b3};
  cuuint32_t es[4] = {1, 1, 1, 1};
  enc(m, CU_TENSOR_MAP_DATA_TYPE_BFLOAT16, 4, const_cast<void*>(base), dims, strides, box, es, CU_TENSOR_MAP_INTERLEAVE_NONE, sw,
      CU_TENSOR_MAP_L2_PROMOTION_L2_128B, CU_TENSOR_MAP_FLOAT_OOB_FILL_NONE);
}

}

extern "C" void kernel_launch(void* const* d_in, const int* in_sizes, int n_in, void* d_out, int out_size) {
  using namespace mla;
  (void)in_sizes; (void)n_in; (void)out_size;
  static EncodeFn enc = nullptr;
  static Scratch* scr = nullptr;
  if (!enc) {
    void* fn = nullptr;
    cudaDriverEntryPointQueryResult st;
    cudaGetDriverEntryPoint("cuTensorMapEncodeTiled", &fn, cudaEnableDefault, &st);
    enc = (EncodeFn)fn;
    cudaFuncSetAttribute(fused_kernel, cudaFuncAttributeMaxDynamicSharedMemorySize, (int)SM_TOTAL);
    void* p = nullptr;
    cudaGetSymbolAddress(&p, g_scr);
    scr = (Scratch*)p;
  }
  Maps m;
  const uint64_t big = 1ull << 24;
  make_map(enc, &m.m[0], d_in[3], 64, 512, 8192, 64, 128, 1, big, 32, 2, 1, CU_TENSOR_MAP_SWIZZLE_128B);
  make_map(enc, &m.m[1], d_in[1], 64, 8, 1024, 8, 128, 1024, 8192, 8, 2, 4, CU_TENSOR_MAP_SWIZZLE_128B);
  make_map(enc, &m.m[2], d_in[4], 64, 512, 8192, 64, 128, 1, big, 32, 2, 1, CU_TENSOR_MAP_SWIZZLE_128B);
  make_map(enc, &m.m[3], d_in[7], 16, 512, 2752, 86, 32, 1, big, 128, 3, 1, CU_TENSOR_MAP_SWIZZLE_32B);
  make_map(enc, &m.m[4], d_in[8], 16, 512, 2752, 86, 32, 1, big, 128, 3, 1, CU_TENSOR_MAP_SWIZZLE_32B);
  make_map(enc, &m.m[5], d_in[9], 64, 1376, 1024, 8, 128, 1, big, 48, 2, 1, CU_TENSOR_MAP_SWIZZLE_128B);
  make_map(enc, &m.m[6], d_in[5], 64, 4096, 1024, 8, 128, 1, big, 32, 2, 1, CU_TENSOR_MAP_SWIZZLE_128B);
  fused_kernel<<<NCTA, NTHREADS, SM_TOTAL>>>((const __nv_bfloat16*)d_in[0], (__nv_bfloat16*)d_out, (const __nv_bfloat16*)d_in[2], scr, m);
}
```
